```python
import torch

def _softmax(x, axis=-1):
    return torch.softmax(x, dim=axis)

def _gelu(x):
    return torch.nn.functional.gelu(x, approximate='tanh')

def _silu(x):
    return torch.nn.functional.silu(x)

def _sigmoid(x):
    return torch.sigmoid(x)

def _layernorm(x, axis=-1, eps=1e-05):
    m = x.mean(dim=axis, keepdim=True)
    v = x.var(dim=axis, keepdim=True, unbiased=False)
    return (x - m) / torch.sqrt(v + eps)

def _scatter_add(tgt, idx, src, axis=0):
    return tgt.clone().index_add_(axis, idx, src)

def _segment_sum(src, seg, n):
    out = torch.zeros((n,) + src.shape[1:], dtype=src.dtype)
    return out.index_add_(0, seg, src)

def _pad(x, pw):
    flat = tuple((v for pair in reversed(pw) for v in pair))
    return torch.nn.functional.pad(x, flat)
kernel_name = 'adaLN_cond__sliding_block__glu_gated_geglu__prompt'

def setup_inputs():

    _w = lambda a: (lambda t: t.to(torch.bfloat16) if t.is_floating_point() else t)(torch.as_tensor(a))

    def _A_setup():
        B, S, D = (1, 2048, 640)
        return {'x': _w((lambda *s: torch.randn(*s, dtype=torch.bfloat16) * 0.05)(B, S, D)), 'wqkv': _w((lambda *s: torch.randn(*s, dtype=torch.bfloat16) * 0.05)(D, 3 * D)), 'wo': _w((lambda *s: torch.randn(*s, dtype=torch.bfloat16) * 0.05)(D, D))}
    _A_in = _A_setup()

    def _B_setup():
        B, S, Dm, Df = (1, 2048, 640, 1536)
        return {'x': _w((lambda *s: torch.randn(*s, dtype=torch.bfloat16) * 0.05)(B, S, Dm)), 'w_gate': _w((lambda *s: torch.randn(*s, dtype=torch.bfloat16) * 0.8)(Dm, Df) * Dm ** (-0.5)), 'w_up': _w((lambda *s: torch.randn(*s, dtype=torch.bfloat16) * 0.8)(Dm, Df) * Dm ** (-0.5)), 'w_down': _w((lambda *s: torch.randn(*s, dtype=torch.bfloat16) * 0.8)(Df, Dm) * Df ** (-0.5))}
    _B_in = _B_setup()
    return {'A_x': _A_in['x'], 'A_wqkv': _A_in['wqkv'], 'A_wo': _A_in['wo'], 'B_x': _B_in['x'], 'B_w_gate': _B_in['w_gate'], 'B_w_up': _B_in['w_up'], 'B_w_down': _B_in['w_down'], 'c': _w((lambda *s: torch.randn(*s, dtype=torch.bfloat16) * 0.2)(1, 640) * 8.0), 'w_mod': _w((lambda *s: torch.randn(*s, dtype=torch.bfloat16) * 0.2)(640, 6 * 640) * 640 ** (-0.5) * 8.0)}

def reference(A_x, A_wqkv, A_wo, B_x, B_w_gate, B_w_up, B_w_down, c, w_mod):

    def _A_ref(x, wqkv, wo):
        B, S, D = x.shape
        H = 32
        Dh = D // H
        W = 256
        qkv = (lambda x, *d: x.permute(*d))((x @ wqkv).reshape(B, S, 3, H, Dh), 2, 0, 3, 1, 4)
        q, k, v = (qkv[0], qkv[1], qkv[2])
        scores = torch.einsum('bhqd,bhkd->bhqk', q, k) * Dh ** (-0.5)
        idx = torch.arange(S)
        mask = (idx[:, None] - idx[None, :] >= 0) & (idx[:, None] - idx[None, :] < W)
        scores = torch.where(mask[None, None], scores, -1000000000.0)
        p = _softmax(scores, axis=-1)
        o = torch.einsum('bhqk,bhkd->bhqd', p, v)
        return (lambda x, *d: x.permute(*d))(o, 0, 2, 1, 3).reshape(B, S, D) @ wo

    def _B_ref(x, w_gate, w_up, w_down):
        g = torch.einsum('bsd,df->bsf', x, w_gate)
        u = torch.einsum('bsd,df->bsf', x, w_up)
        h = _gelu(g) * u
        return torch.einsum('bsf,fd->bsd', h, w_down)
    x = A_x
    mod = (_silu(c) @ w_mod).reshape(c.shape[0], 6, 1, -1)
    sa, ca, ga, sb, cb, gb = (mod[:, 0].clone(), mod[:, 1].clone(), mod[:, 2].clone(), mod[:, 3].clone(), mod[:, 4].clone(), mod[:, 5].clone())
    h = _layernorm(x, axis=-1) * (1 + ca) + sa
    x = x + ga * _A_ref(h, A_wqkv, A_wo)
    h = _layernorm(x, axis=-1) * (1 + cb) + sb
    x = x + gb * _B_ref(h, B_w_gate, B_w_up, B_w_down)
    return x
```

```cpp
#include <cuda_runtime.h>
#include <cuda_bf16.h>
#include <cuda.h>
#include <stdint.h>
#include <math.h>

namespace {

constexpr int S_ = 2048, D_ = 640;
constexpr int NCTA = 128, NHELP = 4;
constexpr float QSCALE = 0.22360679774997896f * 1.4426950408889634f;
constexpr int GEARLY = 2;
constexpr int HDELAY = 2500;
constexpr int TABGO = 0;
constexpr int ZGO = 4;
constexpr int PFW = 0;
constexpr int XEARLY = 2;
constexpr int WEARLY = 2;
constexpr int XINFL2 = 2;

constexpr uint32_t QSTG = 47104;
constexpr uint32_t SM_SP = 188416;
constexpr uint32_t SM_QX = 157696;
constexpr uint32_t SM_RING = 163840;
constexpr uint32_t GSLOT = 16384;
constexpr uint32_t KVH = 36864;
constexpr uint32_t WOB0 = 148480, WOBSZ = 25600, WOB3 = 40960, OA1 = 66560, OA2 = 107520;
constexpr uint32_t OASZ = 40960;
constexpr uint32_t DSTG = 36864;
constexpr uint32_t SM_OST = 184320;
constexpr uint32_t SM_GB = 225280;
constexpr uint32_t SM_TAB = 229376;
constexpr uint32_t SM_AUG = SM_TAB + 512;
constexpr uint32_t SM_BAR = 231936;
constexpr uint32_t SM_TOTAL = 232448;
constexpr uint32_t SB0 = 1024;

enum : int {
  B_MODFULL = 0, B_XFULL = 1, B_RFULL = 5, B_MODFREE = 9, B_MODDONE = 10, B_KVPUB = 11, B_KVFULL = 12, B_AFULL = 16, B_CFULL = 62,
  B_QDONE = 26, B_WOC0 = 27, B_OFULL = 28, B_DFULL = 32,
  B_REMPTY = 37, B_WODONE = 41, B_AFREE = 42, B_GUDONE = 46, B_DEMPTY = 47,
  B_KVW = 52, B_ODONE = 54, B_X1W = 56, B_HHW = 57, B_COUNT = 60
};

__host__ __device__ constexpr int oseq(int i) { return i == 0 ? B_OFULL + 3 : i == 3 ? 63 : 59 + i; }
constexpr int B_AUGFULL = B_MODDONE, B_AUGFREE = B_WOC0;

constexpr int FS = 32;
__device__ __align__(128) uint32_t g_epoch[(NCTA + NHELP) * 32];
constexpr int NREP = 8;
__device__ __align__(128) uint2 g_mod[NREP * 1920];
__device__ __align__(128) uint2 g_st1[S_];
__device__ __align__(128) uint4 g_st2[S_ * 4];
__device__ __align__(1024) uint8_t g_kv[16 * 8 * 4 * 12288];
__device__ __align__(1024) uint8_t g_o[16 * 4 * OASZ];
__device__ __align__(1024) uint8_t g_h2[16 * 10 * 16384];
__device__ __align__(1024) uint8_t g_hh[16 * 24 * 16384];
__device__ __align__(1024) uint8_t g_uv[24 * 2048];
__device__ __align__(128) uint32_t g_uf[32];
__device__ __align__(128) uint32_t g_kvf[(16 * 8 * 8) * FS];
__device__ __align__(128) uint32_t g_of[(16 * 4 * 8) * FS];
__device__ __align__(128) uint32_t g_xf[(16 * 8) * FS];
__device__ __align__(128) uint32_t g_hf[(16 * 4 * 8) * FS];

__device__ __forceinline__ uint32_t smem_u32(const void* p) { return (uint32_t)__cvta_generic_to_shared(p); }
__device__ __forceinline__ void mbar_init(uint32_t b, int c) { asm volatile("mbarrier.init.shared::cta.b64 [%0], %1;" ::"r"(b), "r"(c)); }
__device__ __forceinline__ void mbar_expect(uint32_t b, uint32_t bytes) { asm volatile("mbarrier.arrive.expect_tx.shared::cta.b64 _, [%0], %1;" ::"r"(b), "r"(bytes) : "memory"); }
__device__ __forceinline__ void mbar_arrive(uint32_t b) { asm volatile("mbarrier.arrive.shared::cta.b64 _, [%0];" ::"r"(b) : "memory"); }
constexpr uint32_t SPIN_LIMIT = 1u << 17;
__device__ __forceinline__ void mbar_wait(uint32_t b, uint32_t ph) {
  asm volatile("{\n.reg .pred p;\n.reg .u32 n;\nmov.u32 n, 0;\nLW:\nmbarrier.try_wait.parity.shared::cta.b64 p, [%0], %1;\n@p bra LD;\nadd.u32 n, n, 1;\nsetp.lt.u32 p, n, %2;\n@p bra LW;\nLD:\n}"
               ::"r"(b), "r"(ph), "n"(SPIN_LIMIT) : "memory");
}
__device__ __forceinline__ void mbar_wait_slp(uint32_t b, uint32_t ph) {
  asm volatile("{\n.reg .pred p;\n.reg .u32 n;\nmov.u32 n, 0;\nLW:\nmbarrier.try_wait.parity.shared::cta.b64 p, [%0], %1, %3;\n@p bra LD;\nadd.u32 n, n, 1;\nsetp.lt.u32 p, n, %2;\n@p bra LW;\nLD:\n}"
               ::"r"(b), "r"(ph), "n"(4096), "r"(20000) : "memory");
}
__device__ __forceinline__ void mbar_wait3(uint32_t b0, uint32_t ph0, uint32_t b1, uint32_t ph1, uint32_t b2, uint32_t ph2) {
  asm volatile("{\n.reg .pred p, q, r;\n.reg .u32 n;\nmov.u32 n, 0;\nLW:\nmbarrier.try_wait.parity.shared::cta.b64 p, [%0], %1;\nmbarrier.try_wait.parity.shared::cta.b64 q, [%2], %3;\nmbarrier.try_wait.parity.shared::cta.b64 r, [%4], %5;\nand.pred p, p, q;\nand.pred p, p, r;\n@p bra LD;\nadd.u32 n, n, 1;\nsetp.lt.u32 p, n, %6;\n@p bra LW;\nLD:\n}"
               ::"r"(b0), "r"(ph0), "r"(b1), "r"(ph1), "r"(b2), "r"(ph2), "n"(SPIN_LIMIT) : "memory");
}
__device__ __forceinline__ void mbar_wait2(uint32_t b0, uint32_t ph0, uint32_t b1, uint32_t ph1) {
  asm volatile("{\n.reg .pred p, q;\n.reg .u32 n;\nmov.u32 n, 0;\nLW:\nmbarrier.try_wait.parity.shared::cta.b64 p, [%0], %1;\nmbarrier.try_wait.parity.shared::cta.b64 q, [%2], %3;\nand.pred p, p, q;\n@p bra LD;\nadd.u32 n, n, 1;\nsetp.lt.u32 p, n, %4;\n@p bra LW;\nLD:\n}"
               ::"r"(b0), "r"(ph0), "r"(b1), "r"(ph1), "n"(SPIN_LIMIT) : "memory");
}
__device__ __forceinline__ uint32_t mapa(uint32_t a, uint32_t cta) { uint32_t r; asm("mapa.shared::cluster.u32 %0, %1, %2;" : "=r"(r) : "r"(a), "r"(cta)); return r; }
__device__ __forceinline__ void mbar_arrive_remote(uint32_t rb) { asm volatile("mbarrier.arrive.shared::cluster.b64 _, [%0];" ::"r"(rb) : "memory"); }
__device__ __forceinline__ bool elect() { uint32_t p; asm volatile("{\n.reg .pred P;\nelect.sync _|P, 0xffffffff;\nselp.b32 %0, 1, 0, P;\n}" : "=r"(p)); return p; }
__device__ __forceinline__ void tma2d(uint32_t dst, const CUtensorMap* m, uint32_t bar, int c0, int c1) {
  asm volatile("cp.async.bulk.tensor.2d.shared::cluster.global.mbarrier::complete_tx::bytes [%0], [%1, {%3,%4}], [%2];" ::"r"(dst), "l"(m), "r"(bar), "r"(c0), "r"(c1) : "memory");
}
__device__ __forceinline__ void tma2d_mc(uint32_t dst, const CUtensorMap* m, uint32_t bar, int c0, int c1) {
  asm volatile("cp.async.bulk.tensor.2d.shared::cluster.global.mbarrier::complete_tx::bytes.multicast::cluster [%0], [%1, {%3,%4}], [%2], %5;" ::"r"(dst), "l"(m), "r"(bar), "r"(c0), "r"(c1), "h"((uint16_t)3) : "memory");
}
__device__ __forceinline__ void tma3d_mc(uint32_t dst, const CUtensorMap* m, uint32_t bar, int c0, int c1, int c2) {
  asm volatile("cp.async.bulk.tensor.3d.shared::cluster.global.mbarrier::complete_tx::bytes.multicast::cluster [%0], [%1, {%3,%4,%5}], [%2], %6;" ::"r"(dst), "l"(m), "r"(bar), "r"(c0), "r"(c1), "r"(c2), "h"((uint16_t)3) : "memory");
}
__device__ __forceinline__ void tma5d(uint32_t dst, const CUtensorMap* m, uint32_t bar, int c0, int c1, int c2, int c3, int c4) {
  asm volatile("cp.async.bulk.tensor.5d.shared::cluster.global.mbarrier::complete_tx::bytes [%0], [%1, {%3,%4,%5,%6,%7}], [%2];" ::"r"(dst), "l"(m), "r"(bar), "r"(c0), "r"(c1), "r"(c2), "r"(c3), "r"(c4) : "memory");
}
__device__ __forceinline__ void bulk_g2s(uint32_t dst, const void* src, uint32_t bytes, uint32_t bar) {
  asm volatile("cp.async.bulk.shared::cluster.global.mbarrier::complete_tx::bytes [%0], [%1], %2, [%3];" ::"r"(dst), "l"(src), "r"(bytes), "r"(bar) : "memory");
}
__device__ __forceinline__ void tma_add2d(const CUtensorMap* m, uint32_t src, int c0, int c1) {
  asm volatile("cp.reduce.async.bulk.tensor.2d.global.shared::cta.add.bulk_group [%0, {%2,%3}], [%1];" ::"l"(m), "r"(src), "r"(c0), "r"(c1) : "memory");
}
__device__ __forceinline__ void l2_prefetch(const void* p, uint32_t bytes) { asm volatile("cp.async.bulk.prefetch.L2.global [%0], %1;" ::"l"(p), "r"(bytes) : "memory"); }
__device__ __forceinline__ void prefetch_map(const CUtensorMap* m) { asm volatile("prefetch.tensormap [%0];" ::"l"(m) : "memory"); }
__device__ __forceinline__ uint32_t ld_acq(const uint32_t* p) { uint32_t v; asm volatile("ld.acquire.gpu.global.u32 %0, [%1];" : "=r"(v) : "l"(p) : "memory"); return v; }
__device__ __forceinline__ uint32_t ld_rlx(const uint32_t* p) { uint32_t v; asm volatile("ld.relaxed.gpu.global.u32 %0, [%1];" : "=r"(v) : "l"(p) : "memory"); return v; }
__device__ __forceinline__ void st_rel(uint32_t* p, uint32_t v) { asm volatile(
"st.release.gpu.global.u32 [%0], %1;"
 ::"l"(p), "r"(v) : "memory"); }
__device__ __forceinline__ uint4 ld_ll2(const void* p) {
  uint64_t a, b; asm volatile("ld.relaxed.gpu.global.v2.b64 {%0,%1}, [%2];" : "=l"(a), "=l"(b) : "l"(p) : "memory");
  return make_uint4((uint32_t)a, (uint32_t)(a >> 32), (uint32_t)b, (uint32_t)(b >> 32));
}
__device__ __forceinline__ uint2 ld_ll1(const void* p) {
  uint64_t a; asm volatile("ld.relaxed.gpu.global.b64 %0, [%1];" : "=l"(a) : "l"(p) : "memory");
  return make_uint2((uint32_t)a, (uint32_t)(a >> 32));
}
__device__ __forceinline__ void st_ll2(void* p, uint32_t v0, uint32_t v1, uint32_t tag) {
  uint64_t a = ((uint64_t)tag << 32) | v0, b = ((uint64_t)tag << 32) | v1;
  asm volatile("st.relaxed.gpu.global.v2.b64 [%0], {%1,%2};" ::"l"(p), "l"(a), "l"(b) : "memory");
}
__device__ __forceinline__ void st_ll1(void* p, uint32_t v0, uint32_t tag) {
  const uint64_t a = ((uint64_t)tag << 32) | v0;
  asm volatile("st.relaxed.gpu.global.b64 [%0], %1;" ::"l"(p), "l"(a) : "memory");
}
__device__ __forceinline__ uint4 ld_b128(const void* p) {
  uint64_t a, b;
  asm volatile("{\n.reg .b128 t;\nld.relaxed.gpu.global.b128 t, [%2];\nmov.b128 {%0, %1}, t;\n}" : "=l"(a), "=l"(b) : "l"(p) : "memory");
  return make_uint4((uint32_t)a, (uint32_t)(a >> 32), (uint32_t)b, (uint32_t)(b >> 32));
}
__device__ __forceinline__ void st_b128(void* p, uint32_t x, uint32_t y, uint32_t z, uint32_t w) {
  const uint64_t a = ((uint64_t)y << 32) | x, b = ((uint64_t)w << 32) | z;
  asm volatile("{\n.reg .b128 t;\nmov.b128 t, {%1, %2};\nst.relaxed.gpu.global.b128 [%0], t;\n}" ::"l"(p), "l"(a), "l"(b) : "memory");
}
__device__ __forceinline__ uint32_t nib_put(float v, uint32_t t) { return (__float_as_uint(v) & ~15u) | (t & 15u); }
__device__ __forceinline__ bool nib_ok(uint4 v, uint32_t t) { return (((v.x ^ t) | (v.y ^ (t >> 4)) | (v.z ^ (t >> 8)) | (v.w ^ (t >> 12))) & 15u) == 0; }
__device__ __forceinline__ void warp_poll(const uint32_t* p, uint32_t tag) {
  uint32_t n = 0;
  while (true) {
    uint32_t v = p ? ld_acq(p) : tag;
    if (__all_sync(0xffffffffu, v == tag) || ++n >= SPIN_LIMIT) break;
  }
}
__device__ __forceinline__ uint32_t poll_mask(const uint32_t* p, uint32_t tag) { return __ballot_sync(0xffffffffu, p ? ld_acq(p) == tag : false); }
#define FENCE_ASYNC_SMEM() asm volatile("fence.proxy.async.shared::cta;" ::: "memory")
#define FENCE_ASYNC_GLOBAL() asm volatile("fence.proxy.async.global;" ::: "memory")
#define WG_FENCE() asm volatile("wgmma.fence.sync.aligned;" ::: "memory")
#define WG_COMMIT() asm volatile("wgmma.commit_group.sync.aligned;" ::: "memory")
#define WG_WAIT(n) asm volatile("wgmma.wait_group.sync.aligned %0;" ::"n"(n) : "memory")
#define BAR_SYNC(id, n) asm volatile("bar.sync %0, %1;" ::"n"(id), "n"(n) : "memory")
#define BAR_ARRIVE(id, n) asm volatile("bar.arrive %0, %1;" ::"n"(id), "n"(n) : "memory")

__host__ __device__ constexpr uint64_t mkdesc(uint32_t addr, uint32_t lbo, uint32_t sbo, uint32_t sw) {
  return (uint64_t)((addr & 0x3FFFF) >> 4) | ((uint64_t)(lbo >> 4) << 16) | ((uint64_t)(sbo >> 4) << 32) | ((uint64_t)sw << 62);
}
__device__ __forceinline__ uint64_t dadd(uint64_t d, uint32_t bytes) {
  return (d & 0xFFFFFFFF00000000ull) | (uint32_t)((uint32_t)d + (bytes >> 4));
}

__device__ __forceinline__ void wgmma_rs_n192(float (&d)[96], const uint32_t (&a)[4], uint64_t db) {
  asm volatile("wgmma.mma_async.sync.aligned.m64n192k16.f32.bf16.bf16 {%0, %1, %2, %3, %4, %5, %6, %7, %8, %9, %10, %11, %12, %13, %14, %15, %16, %17, %18, %19, %20, %21, %22, %23, %24, %25, %26, %27, %28, %29, %30, %31, %32, %33, %34, %35, %36, %37, %38, %39, %40, %41, %42, %43, %44, %45, %46, %47, %48, %49, %50, %51, %52, %53, %54, %55, %56, %57, %58, %59, %60, %61, %62, %63, %64, %65, %66, %67, %68, %69, %70, %71, %72, %73, %74, %75, %76, %77, %78, %79, %80, %81, %82, %83, %84, %85, %86, %87, %88, %89, %90, %91, %92, %93, %94, %95}, {%96, %97, %98, %99}, %100, 1, 1, 1, 1;"
    : "+f"(d[0]), "+f"(d[1]), "+f"(d[2]), "+f"(d[3]), "+f"(d[4]), "+f"(d[5]), "+f"(d[6]), "+f"(d[7]), "+f"(d[8]), "+f"(d[9]), "+f"(d[10]), "+f"(d[11]), "+f"(d[12]), "+f"(d[13]), "+f"(d[14]), "+f"(d[15]), "+f"(d[16]), "+f"(d[17]), "+f"(d[18]), "+f"(d[19]), "+f"(d[20]), "+f"(d[21]), "+f"(d[22]), "+f"(d[23]), "+f"(d[24]), "+f"(d[25]), "+f"(d[26]), "+f"(d[27]), "+f"(d[28]), "+f"(d[29]), "+f"(d[30]), "+f"(d[31]), "+f"(d[32]), "+f"(d[33]), "+f"(d[34]), "+f"(d[35]), "+f"(d[36]), "+f"(d[37]), "+f"(d[38]), "+f"(d[39]), "+f"(d[40]), "+f"(d[41]), "+f"(d[42]), "+f"(d[43]), "+f"(d[44]), "+f"(d[45]), "+f"(d[46]), "+f"(d[47]), "+f"(d[48]), "+f"(d[49]), "+f"(d[50]), "+f"(d[51]), "+f"(d[52]), "+f"(d[53]), "+f"(d[54]), "+f"(d[55]), "+f"(d[56]), "+f"(d[57]), "+f"(d[58]), "+f"(d[59]), "+f"(d[60]), "+f"(d[61]), "+f"(d[62]), "+f"(d[63]), "+f"(d[64]), "+f"(d[65]), "+f"(d[66]), "+f"(d[67]), "+f"(d[68]), "+f"(d[69]), "+f"(d[70]), "+f"(d[71]), "+f"(d[72]), "+f"(d[73]), "+f"(d[74]), "+f"(d[75]), "+f"(d[76]), "+f"(d[77]), "+f"(d[78]), "+f"(d[79]), "+f"(d[80]), "+f"(d[81]), "+f"(d[82]), "+f"(d[83]), "+f"(d[84]), "+f"(d[85]), "+f"(d[86]), "+f"(d[87]), "+f"(d[88]), "+f"(d[89]), "+f"(d[90]), "+f"(d[91]), "+f"(d[92]), "+f"(d[93]), "+f"(d[94]), "+f"(d[95])
    : "r"(a[0]), "r"(a[1]), "r"(a[2]), "r"(a[3]), "l"(db));
}
__device__ __forceinline__ void wgmma_rs_n48(float (&d)[24], const uint32_t (&a)[4], uint64_t db) {
  asm volatile("wgmma.mma_async.sync.aligned.m64n48k16.f32.bf16.bf16 {%0, %1, %2, %3, %4, %5, %6, %7, %8, %9, %10, %11, %12, %13, %14, %15, %16, %17, %18, %19, %20, %21, %22, %23}, {%24, %25, %26, %27}, %28, 1, 1, 1, 1;"
    : "+f"(d[0]), "+f"(d[1]), "+f"(d[2]), "+f"(d[3]), "+f"(d[4]), "+f"(d[5]), "+f"(d[6]), "+f"(d[7]), "+f"(d[8]), "+f"(d[9]), "+f"(d[10]), "+f"(d[11]), "+f"(d[12]), "+f"(d[13]), "+f"(d[14]), "+f"(d[15]), "+f"(d[16]), "+f"(d[17]), "+f"(d[18]), "+f"(d[19]), "+f"(d[20]), "+f"(d[21]), "+f"(d[22]), "+f"(d[23])
    : "r"(a[0]), "r"(a[1]), "r"(a[2]), "r"(a[3]), "l"(db));
}
__device__ __forceinline__ void wgmma_ss_n80(float (&d)[40], uint64_t da, uint64_t db) {
  asm volatile("wgmma.mma_async.sync.aligned.m64n80k16.f32.bf16.bf16 {%0, %1, %2, %3, %4, %5, %6, %7, %8, %9, %10, %11, %12, %13, %14, %15, %16, %17, %18, %19, %20, %21, %22, %23, %24, %25, %26, %27, %28, %29, %30, %31, %32, %33, %34, %35, %36, %37, %38, %39}, %40, %41, 1, 1, 1, 0, 1;"
    : "+f"(d[0]), "+f"(d[1]), "+f"(d[2]), "+f"(d[3]), "+f"(d[4]), "+f"(d[5]), "+f"(d[6]), "+f"(d[7]), "+f"(d[8]), "+f"(d[9]), "+f"(d[10]), "+f"(d[11]), "+f"(d[12]), "+f"(d[13]), "+f"(d[14]), "+f"(d[15]), "+f"(d[16]), "+f"(d[17]), "+f"(d[18]), "+f"(d[19]), "+f"(d[20]), "+f"(d[21]), "+f"(d[22]), "+f"(d[23]), "+f"(d[24]), "+f"(d[25]), "+f"(d[26]), "+f"(d[27]), "+f"(d[28]), "+f"(d[29]), "+f"(d[30]), "+f"(d[31]), "+f"(d[32]), "+f"(d[33]), "+f"(d[34]), "+f"(d[35]), "+f"(d[36]), "+f"(d[37]), "+f"(d[38]), "+f"(d[39])
    : "l"(da), "l"(db));
}
__device__ __forceinline__ void wgmma_ss_n128(float (&d)[64], uint64_t da, uint64_t db) {
  asm volatile("wgmma.mma_async.sync.aligned.m64n128k16.f32.bf16.bf16 {%0, %1, %2, %3, %4, %5, %6, %7, %8, %9, %10, %11, %12, %13, %14, %15, %16, %17, %18, %19, %20, %21, %22, %23, %24, %25, %26, %27, %28, %29, %30, %31, %32, %33, %34, %35, %36, %37, %38, %39, %40, %41, %42, %43, %44, %45, %46, %47, %48, %49, %50, %51, %52, %53, %54, %55, %56, %57, %58, %59, %60, %61, %62, %63}, %64, %65, 1, 1, 1, 0, 1;"
    : "+f"(d[0]), "+f"(d[1]), "+f"(d[2]), "+f"(d[3]), "+f"(d[4]), "+f"(d[5]), "+f"(d[6]), "+f"(d[7]), "+f"(d[8]), "+f"(d[9]), "+f"(d[10]), "+f"(d[11]), "+f"(d[12]), "+f"(d[13]), "+f"(d[14]), "+f"(d[15]), "+f"(d[16]), "+f"(d[17]), "+f"(d[18]), "+f"(d[19]), "+f"(d[20]), "+f"(d[21]), "+f"(d[22]), "+f"(d[23]), "+f"(d[24]), "+f"(d[25]), "+f"(d[26]), "+f"(d[27]), "+f"(d[28]), "+f"(d[29]), "+f"(d[30]), "+f"(d[31]), "+f"(d[32]), "+f"(d[33]), "+f"(d[34]), "+f"(d[35]), "+f"(d[36]), "+f"(d[37]), "+f"(d[38]), "+f"(d[39]), "+f"(d[40]), "+f"(d[41]), "+f"(d[42]), "+f"(d[43]), "+f"(d[44]), "+f"(d[45]), "+f"(d[46]), "+f"(d[47]), "+f"(d[48]), "+f"(d[49]), "+f"(d[50]), "+f"(d[51]), "+f"(d[52]), "+f"(d[53]), "+f"(d[54]), "+f"(d[55]), "+f"(d[56]), "+f"(d[57]), "+f"(d[58]), "+f"(d[59]), "+f"(d[60]), "+f"(d[61]), "+f"(d[62]), "+f"(d[63])
    : "l"(da), "l"(db));
}
__device__ __forceinline__ void wgmma_zs_n128(float (&d)[64], uint64_t da, uint64_t db) {
  asm volatile("wgmma.mma_async.sync.aligned.m64n128k16.f32.bf16.bf16 {%0, %1, %2, %3, %4, %5, %6, %7, %8, %9, %10, %11, %12, %13, %14, %15, %16, %17, %18, %19, %20, %21, %22, %23, %24, %25, %26, %27, %28, %29, %30, %31, %32, %33, %34, %35, %36, %37, %38, %39, %40, %41, %42, %43, %44, %45, %46, %47, %48, %49, %50, %51, %52, %53, %54, %55, %56, %57, %58, %59, %60, %61, %62, %63}, %64, %65, 0, 1, 1, 0, 1;"
    : "=f"(d[0]), "=f"(d[1]), "=f"(d[2]), "=f"(d[3]), "=f"(d[4]), "=f"(d[5]), "=f"(d[6]), "=f"(d[7]), "=f"(d[8]), "=f"(d[9]), "=f"(d[10]), "=f"(d[11]), "=f"(d[12]), "=f"(d[13]), "=f"(d[14]), "=f"(d[15]), "=f"(d[16]), "=f"(d[17]), "=f"(d[18]), "=f"(d[19]), "=f"(d[20]), "=f"(d[21]), "=f"(d[22]), "=f"(d[23]), "=f"(d[24]), "=f"(d[25]), "=f"(d[26]), "=f"(d[27]), "=f"(d[28]), "=f"(d[29]), "=f"(d[30]), "=f"(d[31]), "=f"(d[32]), "=f"(d[33]), "=f"(d[34]), "=f"(d[35]), "=f"(d[36]), "=f"(d[37]), "=f"(d[38]), "=f"(d[39]), "=f"(d[40]), "=f"(d[41]), "=f"(d[42]), "=f"(d[43]), "=f"(d[44]), "=f"(d[45]), "=f"(d[46]), "=f"(d[47]), "=f"(d[48]), "=f"(d[49]), "=f"(d[50]), "=f"(d[51]), "=f"(d[52]), "=f"(d[53]), "=f"(d[54]), "=f"(d[55]), "=f"(d[56]), "=f"(d[57]), "=f"(d[58]), "=f"(d[59]), "=f"(d[60]), "=f"(d[61]), "=f"(d[62]), "=f"(d[63])
    : "l"(da), "l"(db));
}
__device__ __forceinline__ void wgmma_rs_n128(float (&d)[64], const uint32_t (&a)[4], uint64_t db) {
  asm volatile("wgmma.mma_async.sync.aligned.m64n128k16.f32.bf16.bf16 {%0, %1, %2, %3, %4, %5, %6, %7, %8, %9, %10, %11, %12, %13, %14, %15, %16, %17, %18, %19, %20, %21, %22, %23, %24, %25, %26, %27, %28, %29, %30, %31, %32, %33, %34, %35, %36, %37, %38, %39, %40, %41, %42, %43, %44, %45, %46, %47, %48, %49, %50, %51, %52, %53, %54, %55, %56, %57, %58, %59, %60, %61, %62, %63}, {%64, %65, %66, %67}, %68, 1, 1, 1, 1;"
    : "+f"(d[0]), "+f"(d[1]), "+f"(d[2]), "+f"(d[3]), "+f"(d[4]), "+f"(d[5]), "+f"(d[6]), "+f"(d[7]), "+f"(d[8]), "+f"(d[9]), "+f"(d[10]), "+f"(d[11]), "+f"(d[12]), "+f"(d[13]), "+f"(d[14]), "+f"(d[15]), "+f"(d[16]), "+f"(d[17]), "+f"(d[18]), "+f"(d[19]), "+f"(d[20]), "+f"(d[21]), "+f"(d[22]), "+f"(d[23]), "+f"(d[24]), "+f"(d[25]), "+f"(d[26]), "+f"(d[27]), "+f"(d[28]), "+f"(d[29]), "+f"(d[30]), "+f"(d[31]), "+f"(d[32]), "+f"(d[33]), "+f"(d[34]), "+f"(d[35]), "+f"(d[36]), "+f"(d[37]), "+f"(d[38]), "+f"(d[39]), "+f"(d[40]), "+f"(d[41]), "+f"(d[42]), "+f"(d[43]), "+f"(d[44]), "+f"(d[45]), "+f"(d[46]), "+f"(d[47]), "+f"(d[48]), "+f"(d[49]), "+f"(d[50]), "+f"(d[51]), "+f"(d[52]), "+f"(d[53]), "+f"(d[54]), "+f"(d[55]), "+f"(d[56]), "+f"(d[57]), "+f"(d[58]), "+f"(d[59]), "+f"(d[60]), "+f"(d[61]), "+f"(d[62]), "+f"(d[63])
    : "r"(a[0]), "r"(a[1]), "r"(a[2]), "r"(a[3]), "l"(db));
}
__device__ __forceinline__ void wgmma_ss_n160(float (&d)[80], uint64_t da, uint64_t db) {
  asm volatile("wgmma.mma_async.sync.aligned.m64n160k16.f32.bf16.bf16 {%0, %1, %2, %3, %4, %5, %6, %7, %8, %9, %10, %11, %12, %13, %14, %15, %16, %17, %18, %19, %20, %21, %22, %23, %24, %25, %26, %27, %28, %29, %30, %31, %32, %33, %34, %35, %36, %37, %38, %39, %40, %41, %42, %43, %44, %45, %46, %47, %48, %49, %50, %51, %52, %53, %54, %55, %56, %57, %58, %59, %60, %61, %62, %63, %64, %65, %66, %67, %68, %69, %70, %71, %72, %73, %74, %75, %76, %77, %78, %79}, %80, %81, 1, 1, 1, 0, 1;"
    : "+f"(d[0]), "+f"(d[1]), "+f"(d[2]), "+f"(d[3]), "+f"(d[4]), "+f"(d[5]), "+f"(d[6]), "+f"(d[7]), "+f"(d[8]), "+f"(d[9]), "+f"(d[10]), "+f"(d[11]), "+f"(d[12]), "+f"(d[13]), "+f"(d[14]), "+f"(d[15]), "+f"(d[16]), "+f"(d[17]), "+f"(d[18]), "+f"(d[19]), "+f"(d[20]), "+f"(d[21]), "+f"(d[22]), "+f"(d[23]), "+f"(d[24]), "+f"(d[25]), "+f"(d[26]), "+f"(d[27]), "+f"(d[28]), "+f"(d[29]), "+f"(d[30]), "+f"(d[31]), "+f"(d[32]), "+f"(d[33]), "+f"(d[34]), "+f"(d[35]), "+f"(d[36]), "+f"(d[37]), "+f"(d[38]), "+f"(d[39]), "+f"(d[40]), "+f"(d[41]), "+f"(d[42]), "+f"(d[43]), "+f"(d[44]), "+f"(d[45]), "+f"(d[46]), "+f"(d[47]), "+f"(d[48]), "+f"(d[49]), "+f"(d[50]), "+f"(d[51]), "+f"(d[52]), "+f"(d[53]), "+f"(d[54]), "+f"(d[55]), "+f"(d[56]), "+f"(d[57]), "+f"(d[58]), "+f"(d[59]), "+f"(d[60]), "+f"(d[61]), "+f"(d[62]), "+f"(d[63]), "+f"(d[64]), "+f"(d[65]), "+f"(d[66]), "+f"(d[67]), "+f"(d[68]), "+f"(d[69]), "+f"(d[70]), "+f"(d[71]), "+f"(d[72]), "+f"(d[73]), "+f"(d[74]), "+f"(d[75]), "+f"(d[76]), "+f"(d[77]), "+f"(d[78]), "+f"(d[79])
    : "l"(da), "l"(db));
}
__device__ __forceinline__ void wgmma_zs_n160(float (&d)[80], uint64_t da, uint64_t db) {
  asm volatile("wgmma.mma_async.sync.aligned.m64n160k16.f32.bf16.bf16 {%0, %1, %2, %3, %4, %5, %6, %7, %8, %9, %10, %11, %12, %13, %14, %15, %16, %17, %18, %19, %20, %21, %22, %23, %24, %25, %26, %27, %28, %29, %30, %31, %32, %33, %34, %35, %36, %37, %38, %39, %40, %41, %42, %43, %44, %45, %46, %47, %48, %49, %50, %51, %52, %53, %54, %55, %56, %57, %58, %59, %60, %61, %62, %63, %64, %65, %66, %67, %68, %69, %70, %71, %72, %73, %74, %75, %76, %77, %78, %79}, %80, %81, 0, 1, 1, 0, 1;"
    : "=f"(d[0]), "=f"(d[1]), "=f"(d[2]), "=f"(d[3]), "=f"(d[4]), "=f"(d[5]), "=f"(d[6]), "=f"(d[7]), "=f"(d[8]), "=f"(d[9]), "=f"(d[10]), "=f"(d[11]), "=f"(d[12]), "=f"(d[13]), "=f"(d[14]), "=f"(d[15]), "=f"(d[16]), "=f"(d[17]), "=f"(d[18]), "=f"(d[19]), "=f"(d[20]), "=f"(d[21]), "=f"(d[22]), "=f"(d[23]), "=f"(d[24]), "=f"(d[25]), "=f"(d[26]), "=f"(d[27]), "=f"(d[28]), "=f"(d[29]), "=f"(d[30]), "=f"(d[31]), "=f"(d[32]), "=f"(d[33]), "=f"(d[34]), "=f"(d[35]), "=f"(d[36]), "=f"(d[37]), "=f"(d[38]), "=f"(d[39]), "=f"(d[40]), "=f"(d[41]), "=f"(d[42]), "=f"(d[43]), "=f"(d[44]), "=f"(d[45]), "=f"(d[46]), "=f"(d[47]), "=f"(d[48]), "=f"(d[49]), "=f"(d[50]), "=f"(d[51]), "=f"(d[52]), "=f"(d[53]), "=f"(d[54]), "=f"(d[55]), "=f"(d[56]), "=f"(d[57]), "=f"(d[58]), "=f"(d[59]), "=f"(d[60]), "=f"(d[61]), "=f"(d[62]), "=f"(d[63]), "=f"(d[64]), "=f"(d[65]), "=f"(d[66]), "=f"(d[67]), "=f"(d[68]), "=f"(d[69]), "=f"(d[70]), "=f"(d[71]), "=f"(d[72]), "=f"(d[73]), "=f"(d[74]), "=f"(d[75]), "=f"(d[76]), "=f"(d[77]), "=f"(d[78]), "=f"(d[79])
    : "l"(da), "l"(db));
}

__device__ __forceinline__ void ldsm4(uint32_t (&r)[4], uint32_t a) {
  asm volatile("ldmatrix.sync.aligned.m8n8.x4.shared.b16 {%0,%1,%2,%3}, [%4];" : "=r"(r[0]), "=r"(r[1]), "=r"(r[2]), "=r"(r[3]) : "r"(a));
}
__device__ __forceinline__ void ldsm4p(uint32_t* r, uint32_t a) {
  asm volatile("ldmatrix.sync.aligned.m8n8.x4.shared.b16 {%0,%1,%2,%3}, [%4];" : "=r"(r[0]), "=r"(r[1]), "=r"(r[2]), "=r"(r[3]) : "r"(a));
}
__device__ __forceinline__ void ldsm2p(uint32_t* r, uint32_t a) {
  asm volatile("ldmatrix.sync.aligned.m8n8.x2.shared.b16 {%0,%1}, [%2];" : "=r"(r[0]), "=r"(r[1]) : "r"(a));
}
__device__ __forceinline__ void ldsm4tp(uint32_t* r, uint32_t a) {
  asm volatile("ldmatrix.sync.aligned.m8n8.x4.trans.shared.b16 {%0,%1,%2,%3}, [%4];" : "=r"(r[0]), "=r"(r[1]), "=r"(r[2]), "=r"(r[3]) : "r"(a));
}
__device__ __forceinline__ void ldsm2tp(uint32_t* r, uint32_t a) {
  asm volatile("ldmatrix.sync.aligned.m8n8.x2.trans.shared.b16 {%0,%1}, [%2];" : "=r"(r[0]), "=r"(r[1]) : "r"(a));
}
__device__ __forceinline__ void stsm4(uint32_t a, const uint32_t (&r)[4]) {
  asm volatile("stmatrix.sync.aligned.m8n8.x4.shared.b16 [%0], {%1,%2,%3,%4};" ::"r"(a), "r"(r[0]), "r"(r[1]), "r"(r[2]), "r"(r[3]));
}
__device__ __forceinline__ uint4 lds128(uint32_t a) { uint4 v; asm volatile("ld.shared.v4.u32 {%0,%1,%2,%3}, [%4];" : "=r"(v.x), "=r"(v.y), "=r"(v.z), "=r"(v.w) : "r"(a)); return v; }
__device__ __forceinline__ void sts32(uint32_t a, uint32_t v) { asm volatile("st.shared.u32 [%0], %1;" ::"r"(a), "r"(v) : "memory"); }
__device__ __forceinline__ uint32_t lds32(uint32_t a) { uint32_t v; asm volatile("ld.shared.u32 %0, [%1];" : "=r"(v) : "r"(a) : "memory"); return v; }
__device__ __forceinline__ void sts64(uint32_t a, uint32_t x, uint32_t y) { asm volatile("st.shared.v2.u32 [%0], {%1,%2};" ::"r"(a), "r"(x), "r"(y) : "memory"); }
__device__ __forceinline__ uint2 lds64(uint32_t a) { uint2 v; asm volatile("ld.shared.v2.u32 {%0,%1}, [%2];" : "=r"(v.x), "=r"(v.y) : "r"(a) : "memory"); return v; }
__device__ __forceinline__ void sts128(uint32_t a, uint4 v) { asm volatile("st.shared.v4.u32 [%0], {%1,%2,%3,%4};" ::"r"(a), "r"(v.x), "r"(v.y), "r"(v.z), "r"(v.w) : "memory"); }
__device__ __forceinline__ void mma16816(float* c, uint32_t a0, uint32_t a1, uint32_t a2, uint32_t a3, uint32_t b0, uint32_t b1) {
  asm("mma.sync.aligned.m16n8k16.row.col.f32.bf16.bf16.f32 {%0,%1,%2,%3}, {%4,%5,%6,%7}, {%8,%9}, {%0,%1,%2,%3};"
      : "+f"(c[0]), "+f"(c[1]), "+f"(c[2]), "+f"(c[3]) : "r"(a0), "r"(a1), "r"(a2), "r"(a3), "r"(b0), "r"(b1));
}
__device__ __forceinline__ void mma1688_c(float* d, uint32_t a0, uint32_t a1, uint32_t b0, const float (&c)[4]) {
  asm("mma.sync.aligned.m16n8k8.row.col.f32.bf16.bf16.f32 {%0,%1,%2,%3}, {%4,%5}, {%6}, {%7,%8,%9,%10};"
      : "=f"(d[0]), "=f"(d[1]), "=f"(d[2]), "=f"(d[3]) : "r"(a0), "r"(a1), "r"(b0), "f"(c[0]), "f"(c[1]), "f"(c[2]), "f"(c[3]));
}
__device__ __forceinline__ uint32_t pack2(float lo, float hi) { uint32_t r; asm("cvt.rn.bf16x2.f32 %0, %1, %2;" : "=r"(r) : "f"(hi), "f"(lo)); return r; }
__device__ __forceinline__ float blo(uint32_t v) { return __uint_as_float(v << 16); }
__device__ __forceinline__ float bhi(uint32_t v) { return __uint_as_float(v & 0xffff0000u); }
__device__ __forceinline__ float ex2(float x) { float y; asm("ex2.approx.ftz.f32 %0, %1;" : "=f"(y) : "f"(x)); return y; }
__device__ __forceinline__ float tanh_ap(float x) { float y; asm("tanh.approx.f32 %0, %1;" : "=f"(y) : "f"(x)); return y; }
__device__ __forceinline__ float bfround(float x) { return blo(pack2(x, 0.f) & 0xffffu); }
__device__ __forceinline__ float rcp_ap(float x) { float y; asm("rcp.approx.ftz.f32 %0, %1;" : "=f"(y) : "f"(x)); return y; }
__device__ __forceinline__ float silu(float c) { return c * rcp_ap(1.f + ex2(c * -1.4426950408889634f)); }
__device__ __forceinline__ void stg32(void* p, uint32_t v) { asm volatile("st.global.u32 [%0], %1;" ::"l"(p), "r"(v) : "memory"); }
__device__ __forceinline__ uint4 ldg128(const void* p) { uint4 v; asm volatile("ld.global.nc.v4.u32 {%0,%1,%2,%3}, [%4];" : "=r"(v.x), "=r"(v.y), "=r"(v.z), "=r"(v.w) : "l"(p)); return v; }
__device__ __forceinline__ uint32_t hmul2(uint32_t a, uint32_t b) { uint32_t d; asm("mul.rn.bf16x2 %0, %1, %2;" : "=r"(d) : "r"(a), "r"(b)); return d; }
struct RowStat { uint32_t nm0, sd0, nm1, sd1; float r0, r1; };
__device__ __forceinline__ void ln_frag(uint32_t (&a)[4], const uint32_t (&x)[4], uint4 t, const RowStat& st) {
  asm volatile("{\n.reg .b32 d0, d1, d2, d3, e0, e1, e2, e3;\n"
               "add.rn.bf16x2 d0, %4, %12;\nadd.rn.bf16x2 d1, %5, %14;\nadd.rn.bf16x2 d2, %6, %12;\nadd.rn.bf16x2 d3, %7, %14;\n"
               "mul.rn.bf16x2 e0, %9, %13;\nmul.rn.bf16x2 e1, %9, %15;\nmul.rn.bf16x2 e2, %11, %13;\nmul.rn.bf16x2 e3, %11, %15;\n"
               "fma.rn.bf16x2 %0, d0, %8, e0;\nfma.rn.bf16x2 %1, d1, %8, e1;\nfma.rn.bf16x2 %2, d2, %10, e2;\nfma.rn.bf16x2 %3, d3, %10, e3;\n}"
               : "=r"(a[0]), "=r"(a[1]), "=r"(a[2]), "=r"(a[3])
               : "r"(x[0]), "r"(x[1]), "r"(x[2]), "r"(x[3]), "r"(t.x), "r"(t.y), "r"(t.z), "r"(t.w), "r"(st.nm0), "r"(st.sd0), "r"(st.nm1), "r"(st.sd1));
}
__device__ __forceinline__ uint32_t stat_word(float mean, float var) {
  float sq; asm("sqrt.approx.ftz.f32 %0, %1;" : "=f"(sq) : "f"(bfround(bfround(var) + 1e-5f)));
  return pack2(-mean, sq);
}
__device__ __forceinline__ void set_stat(RowStat& st, uint32_t w0, uint32_t w1) {
  st.nm0 = __byte_perm(w0, 0, 0x1010); st.sd0 = __byte_perm(w0, 0, 0x3232); st.r0 = rcp_ap(bhi(w0));
  st.nm1 = __byte_perm(w1, 0, 0x1010); st.sd1 = __byte_perm(w1, 0, 0x3232); st.r1 = rcp_ap(bhi(w1));
}
__device__ __forceinline__ void put_table(uint32_t sb, int tid, uint4 sv, uint4 cv) {
  const int p = 2 * tid, ks = p >> 3, w = p & 7;
  const uint32_t a = sb + SM_TAB + (uint32_t)((ks * 4 + (w & 3)) * 16 + (w >> 2) * 8);
  sts32(a, pack2(1.f + blo(cv.x), 1.f + bhi(cv.x)));      sts32(a + 4, sv.x);
  sts32(a + 16, pack2(1.f + blo(cv.z), 1.f + bhi(cv.z))); sts32(a + 20, sv.z);
}
__device__ __forceinline__ void load_gate(uint32_t (&v)[10], const uint2* p, uint32_t tag) {
  uint32_t n = 0; bool ok;
  do {
    ok = true;
#pragma unroll
    for (int t = 0; t < 10; ++t) { const uint2 e = ld_ll1(p + 4 * t); v[t] = e.x; ok = ok && (e.y == tag); }
  } while (!ok && ++n < SPIN_LIMIT);
}
__device__ __forceinline__ bool tagged(uint4 v, uint32_t tag) { return v.y == tag && v.w == tag; }
struct GeluK { float k1, k2, k3; };
__device__ __forceinline__ GeluK gelu_consts(float r) { GeluK k; k.k1 = 0.7978845608f * r; k.k2 = 0.0356774081f * r * r * r; k.k3 = 0.5f * r * r; return k; }
__device__ __forceinline__ float gelu_mul(float ag, float au, const GeluK& k) {
  const float t = tanh_ap(ag * fmaf(ag * ag, k.k2, k.k1));
  const float hu = (ag * au) * k.k3;
  return fmaf(hu, t, hu);
}
__device__ __forceinline__ void geglu_tile(const float (&acc)[64], int t, uint8_t* dst, const GeluK& k0, const GeluK& k1) {
  stg32(dst + t * 2048, pack2(gelu_mul(acc[4 * t], acc[32 + 4 * t], k0), gelu_mul(acc[4 * t + 1], acc[32 + 4 * t + 1], k0)));
  stg32(dst + t * 2048 + 128, pack2(gelu_mul(acc[4 * t + 2], acc[32 + 4 * t + 2], k1), gelu_mul(acc[4 * t + 3], acc[32 + 4 * t + 3], k1)));
}
#define SHX(v, m) __shfl_xor_sync(0xffffffffu, (v), (m))

__host__ __device__ constexpr int bar_count(int i) { return i == B_MODFREE ? 2 : (i >= B_KVW || i == B_QDONE) ? 8 : i >= B_REMPTY ? 4 : i >= B_QDONE ? 2 : 1; }
template <int LO, int HI> __device__ __forceinline__ void init_bars(uint32_t sb) {
#pragma unroll
  for (int i = LO; i < HI; ++i) mbar_init(sb + SM_BAR + 8 * i, bar_count(i));
}

struct Params {
  const __nv_bfloat16 *x, *wqkv, *wo, *wg, *wu, *wd, *c, *wmod;
  __nv_bfloat16* out;
};

__global__ void __cluster_dims__(2, 1, 1) __launch_bounds__(384, 1)
fused_kernel(const __grid_constant__ CUtensorMap mX, const __grid_constant__ CUtensorMap mW64, const __grid_constant__ CUtensorMap mW16,
             const __grid_constant__ CUtensorMap mWo, const __grid_constant__ CUtensorMap mWg, const __grid_constant__ CUtensorMap mWu,
             const __grid_constant__ CUtensorMap mWd, const __grid_constant__ CUtensorMap mMod, const __grid_constant__ CUtensorMap mMod2,
             const __grid_constant__ CUtensorMap mOut, const Params P) {
  extern __shared__ __align__(1024) uint8_t smem[];
  const uint32_t sb = smem_u32(smem);
  const int tid = threadIdx.x, lane = tid & 31;
  const int warp = __shfl_sync(0xffffffffu, tid >> 5, 0);
  if (blockIdx.x < NHELP) {
    const uint32_t tag = ld_rlx(&g_epoch[(NCTA + blockIdx.x) * 32]) + 1;
    const uint32_t hbar = sb + SM_BAR, tab = sb + 196608;
    if (tid == 0) {
#pragma unroll
      for (int i = 0; i < 26; ++i) mbar_init(hbar + 8 * i, (i < 24 && (i % 12) < 6) ? 1 : 4);
    }
    for (int i = tid; i < 320; i += 384) { const uint32_t v = reinterpret_cast<const uint32_t*>(P.c)[i]; const uint32_t sv = pack2(silu(blo(v)), silu(bhi(v))); sts32(tab + i * 4, sv); sts32(tab + 1280 + i * 4, sv); }
    __syncthreads();
    const int wsel = warp < 8 ? warp >> 2 : warp & 1, wk = blockIdx.x * 2 + wsel;
    const uint32_t ring = sb + wsel * 98304, fb = hbar + wsel * 96, eb = fb + 48, pb = hbar + 192 + wsel * 8;
    auto unit = [&](int it) { return it < 2 ? wk + 8 * it : it < 5 ? 20 + 3 * wk + (it - 2) : 16 + wk; };
    auto ucol = [&](int u) { return u < 10 ? 1920 + u * 128 : u < 15 ? u * 128 : u < 20 ? 1280 + u * 128 : (u - 20) * 64; };
    const int nit = wk < 4 ? 6 : 5;
    int slot = 0;

    if (warp == 8 || warp == 9) {
      if (elect()) {
        uint32_t ph = 1;
        const uint32_t t0 = (uint32_t)clock();
        while ((uint32_t)clock() - t0 < (uint32_t)HDELAY) __nanosleep(200);
#pragma unroll 1
        for (int it = 0; it < nit; ++it) {
          const int u = unit(it), col = ucol(u);
#pragma unroll 2
          for (int kb = 0; kb < 10; ++kb) {
            mbar_wait_slp(eb + 8 * slot, ph);
            mbar_expect(fb + 8 * slot, 16384);
            tma2d(ring + slot * 16384, u < 20 ? &mMod2 : &mWg, fb + 8 * slot, col, kb * 64);
            tma2d(ring + slot * 16384 + 8192, u < 20 ? &mMod2 : &mWu, fb + 8 * slot, u < 20 ? col + 64 : col, kb * 64);
            if (++slot == 6) { slot = 0; ph ^= 1; }
          }
        }
      }
    } else if (warp >= 10) {
      if (elect()) {
#pragma unroll 1
        for (int s = 0; s < 3; ++s) { mbar_wait_slp(pb, (uint32_t)(s & 1)); st_rel(&g_uf[3 * wk + s], tag); }
      }
    } else {
      const int g = lane >> 2, q = lane & 3, w4 = warp & 3;
      const uint32_t mytab = tab + 2560 * (1 + wsel);
      const uint32_t boff = (uint32_t)((w4 >> 1) * 8192 + (lane & 15) * 128), bch = (uint32_t)((w4 & 1) * 4 + (lane >> 4));
      uint32_t ph = 0;
#pragma unroll 1
      for (int it = 0; it < nit; ++it) {
        const int u = unit(it);
        if (it == 2) {
          uint2 v[5]; bool ok; uint32_t n = 0;
          do {
            ok = true;
#pragma unroll
            for (int i = 0; i < 5; ++i) { v[i] = ld_ll1(&g_mod[wk * 1920 + 960 + i * 128 + (tid & 127)]); ok = ok && v[i].y == tag; }
          } while (!ok && ++n < SPIN_LIMIT);
#pragma unroll
          for (int i = 0; i < 5; ++i) {
            const int e = i * 128 + (tid & 127);
            sts32(mytab + (e < 320 ? 1280 + e * 4 : (e - 320) * 4), e < 320 ? v[i].x : pack2(1.f + blo(v[i].x), 1.f + bhi(v[i].x)));
          }
          if (wsel) BAR_SYNC(3, 128); else BAR_SYNC(2, 128);
        }

        const uint32_t ta = (u < 20 ? tab : mytab) + (g & 1) * 1280 + q * 4;
        float c[2][4][4];
#pragma unroll
        for (int n = 0; n < 8; ++n) { c[n >> 2][n & 3][0] = c[n >> 2][n & 3][1] = c[n >> 2][n & 3][2] = c[n >> 2][n & 3][3] = 0.f; }
#pragma unroll 1
        for (int kb = 0; kb < 10; ++kb) {
          uint32_t a[8], b[4][8];
#pragma unroll
          for (int i = 0; i < 8; ++i) a[i] = lds32(ta + kb * 128 + i * 16);
          mbar_wait(fb + 8 * slot, ph);
#pragma unroll
          for (int kk = 0; kk < 4; ++kk) {
            const uint32_t ad = ring + slot * 16384 + boff + kk * 2048;
            ldsm4tp(b[kk], ad + ((bch ^ (lane & 7)) << 4)); ldsm4tp(b[kk] + 4, ad + (((bch + 2) ^ (lane & 7)) << 4));
          }
          __syncwarp();
          if (lane == 0) mbar_arrive(eb + 8 * slot);
#pragma unroll
          for (int kk = 0; kk < 4; ++kk)
#pragma unroll
            for (int n = 0; n < 4; ++n) mma16816(c[kk & 1][n], a[2 * kk], a[2 * kk], a[2 * kk + 1], a[2 * kk + 1], b[kk][2 * n], b[kk][2 * n + 1]);
          if (++slot == 6) { slot = 0; ph ^= 1; }
        }

#pragma unroll
        for (int n = 0; n < 4; ++n) {
          float x = c[0][n][0] + c[1][n][0], y = c[0][n][1] + c[1][n][1];
          uint32_t w = pack2(x, y);
          if (u < 20) {
            st_ll1(&g_mod[g * 1920 + ucol(u) / 2 + 16 * w4 + 4 * n + q], w, tag);
          } else {
            if (g >= 2) { x -= blo(w); y -= bhi(w); w = pack2(x, y); }
            if (g >= 4) { x -= blo(w); y -= bhi(w); w = pack2(x, y); }
            stg32(g_uv + (u - 20) * 2048 + (4 * w4 + n) * 128 + lane * 4, g < 6 ? w : 0u);
          }
        }
        if (u >= 20) { __syncwarp(); if (lane == 0) mbar_arrive(pb); }
      }
    }
    __syncthreads();
    if (tid == 0) g_epoch[(NCTA + blockIdx.x) * 32] = tag;
    return;
  }
  const int bid = blockIdx.x - NHELP, rank = bid & 1, j = (bid >> 1) & 7, r = ((bid >> 4) << 1) | rank;
  const int kb0 = (5 * j + 3) >> 2;
  auto BAR = [&](int i) -> uint32_t { return sb + SM_BAR + 8u * (uint32_t)i; };

  if (__builtin_expect(warp == 10, 1) && elect()) {
#pragma unroll
    for (int i = 0; i < 5; ++i) l2_prefetch(P.wmod + (size_t)(i * 128 + bid) * 3840, 2560);
  }
  if (__builtin_expect(warp == 9, 1) && elect()) {
    mbar_init(BAR(B_MODFULL), 1); mbar_init(BAR(B_CFULL), 1);
    mbar_expect(BAR(B_CFULL), 1280);
    bulk_g2s(sb + SM_SP + 20480, P.c, 1280, BAR(B_CFULL));
    if (bid < 80) {
      mbar_expect(BAR(B_MODFULL), 20480);
#pragma unroll
      for (int i = 0; i < 5; ++i) tma2d(sb + SM_SP + i * 4096, &mMod, BAR(B_MODFULL), bid * 16, i * 128);
    } else mbar_arrive(BAR(B_MODFULL));
  }

  if (warp >= 8) {
    if (elect()) {
      if (warp == 9) init_bars<B_XFULL, B_KVFULL>(sb);
      else if (warp == 8) { init_bars<B_AFREE, B_COUNT>(sb); if ((sb & 0x3FFFFu) != SB0) __trap(); }
      else if (warp == 10) { init_bars<B_KVFULL, B_QDONE>(sb); mbar_init(BAR(60), 2); mbar_init(BAR(61), 2); mbar_init(BAR(63), 2); }
      else init_bars<B_QDONE, B_AFREE>(sb);
      asm volatile("fence.mbarrier_init.release.cluster;" ::: "memory");
    }
    BAR_SYNC(0, 384);
    asm volatile("barrier.cluster.arrive.relaxed.aligned;" ::: "memory");
    asm volatile("setmaxnreg.dec.sync.aligned.u32 40;");
    if (warp == 8) {
      asm volatile("barrier.cluster.wait.acquire.aligned;" ::: "memory");
      if (elect()) {
#pragma unroll 1
        for (int u = 0; u < 10; ++u) {
          const int slot = u & 3;
          if (u == WEARLY) mbar_wait_slp(BAR(B_MODFREE), 0);
          mbar_wait_slp(BAR(B_REMPTY + slot), (uint32_t)(((u >> 2) & 1) ^ 1));
          const uint32_t fb = BAR(B_RFULL + slot), dst = sb + slot * QSTG + 16384;
          mbar_expect(fb, 30720);
          const int kr = u * 64 + rank * 32;
          tma3d_mc(dst + rank * 12288, &mW64, fb, 80 * j, kr, 0);
          tma3d_mc(dst + 24576 + rank * 3072, &mW16, fb, 80 * j + 64, kr, 0);
        }
        l2_prefetch((const uint8_t*)P.wo + bid * 6400, 6400);
        l2_prefetch((const uint8_t*)P.wd + bid * 15360, 15360);
        prefetch_map(&mWo); prefetch_map(&mWg); prefetch_map(&mWu); prefetch_map(&mWd); prefetch_map(&mOut);
        mbar_wait_slp(BAR(B_MODDONE), 0);
        mbar_wait_slp(BAR(B_KVW + 1), 0);
#pragma unroll 1
        for (int c = 0; c < 4; ++c) {
          mbar_wait_slp(BAR(c < 2 ? B_KVFULL + 3 : B_ODONE), 0);
          const uint32_t fb = BAR(B_OFULL + (c < 2 ? c : 2));
          mbar_expect(fb, WOBSZ);
          tma5d(sb + (c == 3 ? WOB3 : WOB0 + c * WOBSZ), &mWo, fb, 0, 0, 4 * (c & 1), 5 * j, c >> 1);
        }
        mbar_wait_slp(BAR(B_WODONE), 0); mbar_wait_slp(BAR(B_X1W), 0);
        {
          const CUtensorMap* m = rank ? &mWu : &mWg;
          int kr = kb0 * 64, col = 192 * j, cnt = 0;
#pragma unroll 1
          for (int u = 10; u < 40; ++u) {
            const int slot = u & 3;
            if (u == 10 + GEARLY) mbar_wait_slp(BAR(B_KVPUB), 1);
            mbar_wait_slp(BAR(B_REMPTY + slot), (uint32_t)(((u >> 2) & 1) ^ 1));
            mbar_expect(BAR(B_RFULL + slot), GSLOT);
            tma2d_mc(sb + SM_RING + slot * GSLOT + rank * 8192, m, BAR(B_RFULL + slot), col, kr);
            kr += 64; if (kr == 640) kr = 0;
            if (++cnt == 10) { cnt = 0; col += 64; }
          }
        }
        int slot = 0; uint32_t ph = 1;
#pragma unroll 1
        for (int i = 0; i < 12; ++i) {
          mbar_wait_slp(BAR(i < 4 ? B_AFREE + i : i == 4 ? B_GUDONE : B_DEMPTY + slot), i < 5 ? 0u : ph);
          mbar_expect(BAR(B_DFULL + slot), 20480);
          tma3d_mc(sb + slot * DSTG + 16384 + rank * 10240, &mWd, BAR(B_DFULL + slot), 0, (12 * (j & 1) + 3 * (i & 3) + (i >> 2)) * 64 + rank * 32, 5 * (j >> 1));
          if (++slot == 5) { slot = 0; ph ^= 1; }
        }
      }
    } else if (warp == 9) {
#pragma unroll 1
      for (int u = 0; u < 12; ++u) {
        const int slot = u & 3;
        if (u == XEARLY) mbar_wait_slp(BAR(B_MODFREE), 0);
        if (u >= 4) { const int v = u == 4 ? 0 : u == 11 ? 7 : u - 5; mbar_wait_slp(BAR(B_REMPTY + (v & 3)), (uint32_t)((v >> 2) & 1)); }
        if (elect()) { mbar_expect(BAR(B_XFULL + slot), 16384); tma2d(sb + slot * QSTG, &mX, BAR(B_XFULL + slot), (u < 10 ? u : ((5 * j) >> 2) + u - 10) * 64, r * 128); }
      }
      __syncwarp();
      const uint32_t tag = ld_rlx(&g_epoch[bid * 32]) + 1;
      asm volatile("barrier.cluster.wait.acquire.aligned;" ::: "memory");
      mbar_wait_slp(BAR(B_QDONE), 0);
#pragma unroll 1
      for (int hp = 0; hp < 2; ++hp) {
        if (r < 2) {
          const int ng = (2 - r) * 16;
#pragma unroll 1
          for (int i = lane; i < ng * 24; i += 32) {
            const uint32_t bias = ((i >> 3) % 6) >= 4 ? 0xFF80FF80u : 0u, a = sb + hp * 2 * KVH + i * 16;
            sts128(a, make_uint4(0, 0, bias, bias)); sts128(a + KVH, make_uint4(bias, bias, 0, 0));
            sts128(a + 18432, make_uint4(0, 0, 0, 0)); sts128(a + KVH + 18432, make_uint4(0, 0, 0, 0));
          }
          __syncwarp();
        }
        if (elect()) { mbar_expect(BAR(B_KVFULL + 2 * hp), (r >= 2 ? 2 : r) * 12288); mbar_expect(BAR(B_KVFULL + 2 * hp + 1), (r >= 2 ? 2 : r) * 12288); }
        const int rb = r - 2 + lane;
        const uint32_t* fp = (lane < 2 && rb >= 0) ? &g_kvf[((rb * 8 + j) * 8 + hp) * FS] : nullptr;
        uint32_t todo = r >= 2 ? 3u : r == 1 ? 2u : 0u;
        for (uint32_t n = 0; todo && n < SPIN_LIMIT; ++n) {
          uint32_t m = poll_mask(fp, tag) & todo;
          todo &= ~m;
          if (m && elect()) {
            FENCE_ASYNC_GLOBAL();
            for (; m; m &= m - 1) {
              const int b = __ffs(m) - 1;
              const uint8_t* src = g_kv + (size_t)(((r - 2 + b) * 8 + j) * 4 + 2 * hp) * 12288;
              const uint32_t dst = sb + hp * 2 * KVH + b * 6144;
              bulk_g2s(dst, src, 6144, BAR(B_KVFULL + 2 * hp)); bulk_g2s(dst + KVH, src + 12288, 6144, BAR(B_KVFULL + 2 * hp + 1));
              bulk_g2s(dst + 18432, src + 6144, 6144, BAR(B_KVFULL + 2 * hp)); bulk_g2s(dst + KVH + 18432, src + 18432, 6144, BAR(B_KVFULL + 2 * hp + 1));
            }
          }
          __syncwarp();
        }

      }
      mbar_wait_slp(BAR(B_ODONE), 0);
      warp_poll(lane < 8 ? &g_of[((r * 4) * 8 + lane) * FS] : nullptr, tag);
      FENCE_ASYNC_GLOBAL();
      if (elect()) { mbar_expect(BAR(B_OFULL), OASZ); bulk_g2s(sb, g_o + (size_t)(r * 4) * OASZ, OASZ, BAR(B_OFULL)); }
      mbar_wait_slp(BAR(B_ODONE + 1), 0);
      if (elect()) {
        mbar_expect(BAR(B_OFULL + 1), OASZ); bulk_g2s(sb + OA1, g_o + (size_t)(r * 4 + 1) * OASZ, OASZ, BAR(B_OFULL + 1));
      }
      {
        uint32_t todo = 0x55u;
        int seq = 0;
        for (uint32_t n = 0; todo && n < SPIN_LIMIT; ++n) {
          uint32_t m = poll_mask(lane < 8 ? &g_of[((r * 4 + 1) * 8 + lane) * FS] : nullptr, tag);
          m = m & (m >> 1) & todo;
          todo &= ~m;
          if (m) FENCE_ASYNC_GLOBAL();
          for (; m; m &= m - 1, ++seq) {
            const uint32_t p = (uint32_t)(__ffs(m) - 1) >> 1, fb = BAR(seq == 0 ? oseq(0) : seq == 3 ? oseq(3) : 59 + seq);
            if (seq == 2) mbar_wait_slp(BAR(B_WOC0), 0);
            if (elect()) {
              mbar_expect(fb, 20480);
              bulk_g2s(sb + (seq < 2 ? OA2 : 0u) + (seq & 1) * 20480, g_o + (size_t)(r * 4 + 2) * OASZ + p * 20480, 20480, fb);
              sts32(sb + SM_GB + seq * 4, ((p & 2) ? WOB3 : WOB0 + 2 * WOBSZ) + (p & 1) * 2560); sts32(sb + SM_TAB + 504, 0u);
              mbar_arrive(fb);
            }
            __syncwarp();
          }
        }

      }
      mbar_wait_slp(BAR(B_X1W), 0);
      {
        uint32_t m = 0; int kb = kb0;
#pragma unroll 1
        for (int i = 0; i < 10; ++i) {
          const uint32_t need = (1u << ((4 * kb) / 5)) | (1u << ((64 * kb + 63) / 80));
          if ((m & need) != need) {
            for (uint32_t n = 0; (m & need) != need && n < SPIN_LIMIT; ++n) m = poll_mask(lane < 8 ? &g_xf[(r * 8 + lane) * FS] : nullptr, tag);
            FENCE_ASYNC_GLOBAL();
          }

          if (i >= XINFL2) mbar_wait_slp(BAR(B_AFULL + i - XINFL2), 1);
          if (elect()) { mbar_expect(BAR(B_AFULL + i), 16384); bulk_g2s(sb + i * 16384, g_h2 + (size_t)(r * 10 + kb) * 16384, 16384, BAR(B_AFULL + i)); }
          __syncwarp();
          if (++kb == 10) kb = 0;
        }
      }
      int slot = 0; uint32_t ph = 1;
#pragma unroll 1
      for (int i = 0; i < 8; ++i) {
        if (i == 0 || i == 3) {
          mbar_wait_slp(BAR(B_HHW + (i & 1)), 0);
          warp_poll(lane < 6 ? &g_hf[((r * 4 + (i & 1)) * 8 + (lane < 4 ? 4 * (j & 1) + lane : j ^ (lane & 1))) * FS] : nullptr, tag);

          FENCE_ASYNC_GLOBAL();
        }
        mbar_wait_slp(BAR(i < 4 ? B_AFREE + i : i == 4 ? B_GUDONE : B_DEMPTY + slot), i < 5 ? 0u : ph);
        if (elect()) {
          mbar_expect(BAR(B_DFULL + slot), 16384);
          bulk_g2s(sb + slot * DSTG, g_hh + (size_t)(r * 24 + 12 * (j & 1) + 3 * (i & 3) + (i >> 2)) * 16384, 16384, BAR(B_DFULL + slot));
        }
        __syncwarp();
        if (++slot == 5) { slot = 0; ph ^= 1; }
      }
    } else if (warp == 10) {
      const uint32_t tag = ld_rlx(&g_epoch[bid * 32]) + 1;
      asm volatile("barrier.cluster.wait.acquire.aligned;" ::: "memory");
      {
        const uint2* mp = g_mod + ((bid >> 1) ^ (bid >> 4)) % NREP * 1920 + 2 * lane;
#pragma unroll 1
        for (int p = 0; p < 5; ++p) {
          uint4 sv, cv, sw = ld_ll2(mp + 64 * p), cw = ld_ll2(mp + 320 + 64 * p);
          for (uint32_t n = 0; n < SPIN_LIMIT; ++n) {
            if (p == 0 || n) { __nanosleep(60); sv = ld_ll2(mp + 64 * p); cv = ld_ll2(mp + 320 + 64 * p); }
            if (__all_sync(0xffffffffu, tagged(sw, tag) && tagged(cw, tag))) { sv = sw; cv = cw; break; }
            if (!(p == 0 || n)) { sv = sw; cv = cw; }
            sw = ld_ll2(mp + 64 * p); cw = ld_ll2(mp + 320 + 64 * p);
            if (__all_sync(0xffffffffu, tagged(sv, tag) && tagged(cv, tag))) break;
          }
          put_table(sb, p * 32 + lane, sv, cv);
          __syncwarp();
          if (lane == 0) { mbar_arrive(BAR(B_AFULL + 2 * p)); mbar_arrive(BAR(B_AFULL + 2 * p + 1)); if (p == TABGO) mbar_arrive(BAR(B_MODFREE)); }

        }
      }
#pragma unroll 1
      for (int i = 0; i < 8; ++i) {
        uint32_t* f = i < 2 ? &g_kvf[((r * 8 + j) * 8 + i) * FS] : i < 4 ? &g_of[((r * 4 + i - 2) * 8 + j) * FS] : i == 4 ? &g_xf[(r * 8 + j) * FS] : &g_hf[((r * 4 + i - 5) * 8 + j) * FS];
        if (i == 5) {
          mbar_wait_slp(BAR(B_AFULL + ZGO), 1);
          uint8_t* zp = reinterpret_cast<uint8_t*>(P.out + (size_t)(r * 128 + lane / 10) * D_ + 80 * j) + (lane % 10) * 16;
#pragma unroll 4
          for (int k = 0; k < 43; ++k) if (lane < 30 && 3 * k + lane / 10 < 128) *reinterpret_cast<uint4*>(zp + k * 3 * D_ * 2) = make_uint4(0, 0, 0, 0);
          __syncwarp();
        }
        mbar_wait_slp(BAR(B_KVW + i), 0);
        if (elect()) {

          st_rel(f, tag);
          if (i == 0 || i == 4) mbar_arrive(BAR(B_KVPUB));

        }
        __syncwarp();
      }
    } else {
      const uint32_t tag = ld_rlx(&g_epoch[bid * 32]) + 1;
      asm volatile("barrier.cluster.wait.acquire.aligned;" ::: "memory");
      mbar_wait_slp(BAR(B_XFULL + PFW), 0);
      if (elect()) l2_prefetch((const uint8_t*)P.wqkv + bid * 19200, 19200);
      if (elect()) mbar_arrive(BAR(B_MODDONE));
      mbar_wait_slp(BAR(B_ODONE), 0);
#pragma unroll 1
      for (int s = 0; s < 3; ++s) {
        if (s == 1) mbar_wait_slp(BAR(B_WOC0), 0);
        if (s) mbar_wait_slp(BAR(B_AUGFREE), (uint32_t)(s & 1));
        warp_poll(lane == 0 ? &g_uf[3 * j + s] : nullptr, tag);
        FENCE_ASYNC_GLOBAL();
        if (elect()) { mbar_expect(BAR(B_AUGFULL), 2048); bulk_g2s(sb + SM_AUG, g_uv + (size_t)(3 * j + s) * 2048, 2048, BAR(B_AUGFULL)); }
        __syncwarp();
      }
      mbar_wait_slp(BAR(B_HHW + 2), 0);
      {
        const uint2* gp = g_mod + ((bid >> 1) ^ (bid >> 4)) % NREP * 1920 + 1600 + 80 * (j >> 1);
        uint2 v[3]; bool ok; uint32_t n = 0;
        do {
          ok = true;
#pragma unroll
          for (int i = 0; i < 3; ++i) { v[i] = ld_ll1(gp + (i * 32 + lane < 80 ? i * 32 + lane : 0)); ok = ok && v[i].y == tag; }
        } while (!ok && ++n < SPIN_LIMIT);
#pragma unroll
        for (int i = 0; i < 3; ++i) sts32(sb + SM_GB + (i * 32 + lane) * 4, v[i].x);
        __syncwarp();
      }
      uint32_t m = 0;
#pragma unroll 1
      for (int i = 8; i < 12; ++i) {
        const int slot = i % 5;
        if (!((m >> (i & 3)) & 1)) {
          for (uint32_t n = 0; !((m >> (i & 3)) & 1) && n < SPIN_LIMIT; ++n) m = poll_mask(lane < 4 ? &g_hf[((r * 4 + 2) * 8 + 4 * (j & 1) + lane) * FS] : nullptr, tag);
          FENCE_ASYNC_GLOBAL();
        }

        mbar_wait_slp(BAR(B_DEMPTY + slot), i < 10 ? 0u : 1u);
        if (elect()) {
          mbar_expect(BAR(B_DFULL + slot), 16384);
          bulk_g2s(sb + slot * DSTG, g_hh + (size_t)(r * 24 + 12 * (j & 1) + 3 * (i & 3) + 2) * 16384, 16384, BAR(B_DFULL + slot));
        }
        __syncwarp();
      }
    }
  } else {
    const int wg = warp >> 2;
    const int g = lane >> 2, q = lane & 3;
    const bool leader = (tid & 127) == 0;
    const uint32_t rsb = mapa(sb, (uint32_t)(rank ^ 1));
    auto release = [&](int bar) { if (leader) { mbar_arrive(sb + SM_BAR + 8u * (uint32_t)bar); mbar_arrive_remote(rsb + SM_BAR + 8u * (uint32_t)bar); } };
    RowStat st;
    uint32_t tag;
    const uint2* modp = g_mod + ((bid >> 1) ^ (bid >> 4)) % NREP * 1920;

    {
      uint4 xv[2][5];
      const int srow = r * 128 + j * 16 + (warp & 3) * 4 + (lane >> 4) * 2;
      tag = ld_rlx(&g_epoch[bid * 32]) + 1;
      const uint2* stp = &g_st1[r * 128 + 2 * (tid & 63)];
      BAR_SYNC(0, 384);
      if (wg == 1) {
#pragma unroll
        for (int e = 0; e < 2; ++e)
#pragma unroll
          for (int i = 0; i < 5; ++i) xv[e][i] = ldg128(P.x + (size_t)(srow + e) * D_ + (i * 16 + (lane & 15)) * 8);
      }
      asm volatile("barrier.cluster.arrive.relaxed.aligned;" ::: "memory");
      asm volatile("setmaxnreg.inc.sync.aligned.u32 232;");

      if (wg == 1) {
        float sm[2], sq[2];
#pragma unroll
        for (int e = 0; e < 2; ++e) {
          const float z = __shfl_sync(0xffffffffu, blo(xv[e][0].x), lane & 16);
          float s0 = 0.f, s1 = 0.f, v0 = 0.f, v1 = 0.f;
#pragma unroll
          for (int i = 0; i < 5; ++i) {
            const uint32_t w[4] = {xv[e][i].x, xv[e][i].y, xv[e][i].z, xv[e][i].w};
#pragma unroll
            for (int k = 0; k < 4; ++k) { const float a = blo(w[k]) - z, b = bhi(w[k]) - z; s0 += a; s1 += b; v0 = fmaf(a, a, v0); v1 = fmaf(b, b, v1); }
          }
          s0 += s1; v0 += v1;
#pragma unroll
          for (int o = 8; o; o >>= 1) { s0 += SHX(s0, o); v0 += SHX(v0, o); }
          s0 *= (1.f / D_);
          sm[e] = z + s0; sq[e] = fmaxf(fmaf(v0, 1.f / D_, -s0 * s0), 0.f);
        }
        if ((lane & 15) == 0) st_ll2(&g_st1[srow], stat_word(sm[0], sq[0]), stat_word(sm[1], sq[1]), tag);

      } else {
        mbar_wait(BAR(B_CFULL), 0);
#pragma unroll
        for (int i = 0; i < 3; ++i) {
          const uint32_t a = sb + SM_SP + 20480 + (i * 128 + tid) * 4;
          if (i * 128 + tid < 320) { const uint32_t v = lds32(a); sts32(a, pack2(silu(blo(v)), silu(bhi(v)))); }
        }
        BAR_SYNC(1, 128);
        if (bid < 80) {
          uint32_t sa[10][2];
#pragma unroll
          for (int i = 0; i < 10; ++i) { sa[i][0] = lds32(sb + SM_SP + 20480 + (warp * 10 + i) * 32 + q * 4); sa[i][1] = lds32(sb + SM_SP + 20480 + (warp * 10 + i) * 32 + 16 + q * 4); }
          float c0[4] = {0.f, 0.f, 0.f, 0.f}, c1[4] = {0.f, 0.f, 0.f, 0.f};
          mbar_wait(BAR(B_MODFULL), 0);

#pragma unroll
          for (int i = 0; i < 10; ++i) {
            uint32_t b[4];
            ldsm4tp(b, sb + SM_SP + (warp * 160 + i * 16 + (lane & 15)) * 32 + (lane >> 4) * 16);
            mma16816(c0, sa[i][0], sa[i][0], sa[i][1], sa[i][1], b[0], b[1]); mma16816(c1, sa[i][0], sa[i][0], sa[i][1], sa[i][1], b[2], b[3]);
          }
          if (lane < 8) {
            sts32(sb + SM_SP + 21760 + (lane * 8 + warp) * 4, __float_as_uint(lane < 4 ? c0[0] : c1[0]));
            sts32(sb + SM_SP + 21760 + (lane * 8 + 4 + warp) * 4, __float_as_uint(lane < 4 ? c0[1] : c1[1]));
          }
          if (warp == 3) {
            BAR_SYNC(1, 128);
            const uint4 a = lds128(sb + SM_SP + 21760 + (lane & 15) * 16);
            const float t = (__uint_as_float(a.x) + __uint_as_float(a.y)) + (__uint_as_float(a.z) + __uint_as_float(a.w));
            const uint32_t pr = pack2(t, SHX(t, 1));
            const uint32_t p0 = __shfl_sync(0xffffffffu, pr, (lane & 3) * 4), p1 = __shfl_sync(0xffffffffu, pr, (lane & 3) * 4 + 2);
            st_ll2(&g_mod[(lane >> 2) * 1920 + bid * 8 + (lane & 3) * 2], p0, p1, tag);

          } else BAR_ARRIVE(1, 128);
        }
      }
      {
        uint32_t n = 0;
        if (tid >= 192) {
          uint4 stv;
          do { stv = ld_ll2(stp); } while (!tagged(stv, tag) && ++n < SPIN_LIMIT);
          sts64(sb + SM_SP + 22528 + (tid - 192) * 8, stv.x, stv.z);
        }
      }
      asm volatile("barrier.cluster.wait.acquire.aligned;" ::: "memory");
      BAR_SYNC(6, 256);
      if (tid == 0) mbar_arrive(BAR(B_MODFREE));
      set_stat(st, lds32(sb + SM_SP + 22528 + (warp * 16 + g) * 4), lds32(sb + SM_SP + 22528 + (warp * 16 + g + 8) * 4));
    }

    const int mi = lane >> 3, l7 = lane & 7;
    uint32_t qf[4][6];
    uint32_t xs[5][4];
    {
      float accW[96], accN[24];
#pragma unroll
      for (int i = 0; i < 96; ++i) accW[i] = 0.f;
#pragma unroll
      for (int i = 0; i < 24; ++i) accN[i] = 0.f;
      const uint32_t tabq = sb + SM_TAB + q * 16;
      const uint32_t arow = sb + (uint32_t)(warp * 16 + (mi & 1) * 8 + l7) * 128 + (uint32_t)(((mi >> 1) ^ l7) << 4);
      constexpr uint64_t dW = mkdesc(SB0 + 16384, 4096, 1024, 1), dN = mkdesc(SB0 + 16384 + 24576, 1024, 256, 3);
      uint32_t af[2][4][4], raw[4][4]; uint4 tb[4];
      auto fetch = [&](int kb) {
#pragma unroll
        for (int i = 0; i < 4; ++i) { ldsm4(raw[i], (arow ^ (uint32_t)(i << 5)) + (kb & 3) * QSTG); tb[i] = lds128(tabq + kb * 256 + i * 64); }
      };
      auto xform_fetch = [&](uint32_t (&a)[4][4], int kb) {
#pragma unroll
        for (int i = 0; i < 4; ++i) {
          ln_frag(a[i], raw[i], tb[i], st);
          ldsm4(raw[i], (arow ^ (uint32_t)(i << 5)) + (kb & 3) * QSTG); tb[i] = lds128(tabq + kb * 256 + i * 64);
        }
      };
      mbar_wait2(BAR(B_XFULL), 0, BAR(B_AFULL), 0);

      fetch(0);
      mbar_wait2(BAR(B_XFULL + 1), 0, BAR(B_RFULL), 0);
      xform_fetch(af[0], 1);
#pragma unroll 1
      for (int kp = 0; kp < 5; ++kp) {
#pragma unroll
        for (int e = 0; e < 2; ++e) {
          const int kb = 2 * kp + e, slot = kb & 3;
          const int k1 = kb < 9 ? kb + 1 : 9, k2 = kb < 8 ? kb + 2 : 9;
          const uint64_t dw = dadd(dW, slot * QSTG), dn = dadd(dN, slot * QSTG);
          WG_FENCE();
#pragma unroll
          for (int kk = 0; kk < 4; ++kk) {
            wgmma_rs_n192(accW, af[e][kk], dadd(dw, (kk >> 1) * 12288 + (kk & 1) * 2048));
            wgmma_rs_n48(accN, af[e][kk], dadd(dn, (kk >> 1) * 3072 + (kk & 1) * 512));
          }
          WG_COMMIT();
          WG_WAIT(1);
          if (kb > 0) release(B_REMPTY + ((kb + 3) & 3));
          mbar_wait3(BAR(B_XFULL + (k2 & 3)), (uint32_t)((k2 >> 2) & 1), BAR(B_AFULL + k2), 0, BAR(B_RFULL + (k1 & 3)), (uint32_t)((k1 >> 2) & 1));
          xform_fetch(af[e ^ 1], k2);
        }
      }
      mbar_wait2(BAR(B_XFULL + 2), 0, BAR(B_XFULL + 3), 0);
#pragma unroll
      for (int i = 0; i < 5; ++i) { const int kk = (j & 3) + i; ldsm4(xs[i], (arow ^ (uint32_t)((kk & 3) << 5)) + (2 + (kk >> 2)) * QSTG); }
      WG_WAIT(0);
      release(B_REMPTY + 1);
      asm volatile("" ::"r"(xs[0][0]), "r"(xs[1][0]), "r"(xs[2][0]), "r"(xs[3][0]), "r"(xs[4][0]) : "memory");
      __syncwarp();
      if (lane == 0) mbar_arrive(BAR(B_QDONE));

      uint32_t pk[3][20];
      auto packt = [&](int p, int t, float f0, float f1) {
        const float* a = t < 8 ? &accW[32 * p + 4 * t] : &accN[8 * p + 4 * (t - 8)];
        pk[p][2 * t] = pack2(a[0] * f0, a[1] * f0); pk[p][2 * t + 1] = pack2(a[2] * f1, a[3] * f1);
      };
#pragma unroll
      for (int t = 0; t < 5; ++t) { packt(1, t, st.r0, st.r1); packt(2, t, st.r0, st.r1); }
      uint8_t* kvdst = g_kv + (size_t)((r * 8 + j) * 4) * 12288 + warp * 768 + lane * 4;
#pragma unroll
      for (int h = 0; h < 4; ++h) {
        const int t0 = 5 * (h >> 1);
        const int c0 = (h & 1) ? t0 + 3 : t0, c1 = c0 + 1, c2 = t0 + 2;
        const bool own = (h & 1) ? (q >= 2) : (q < 2);
        uint8_t* d = kvdst + h * 12288;
        if (h == 2) mbar_wait(BAR(B_KVPUB), 0);
#pragma unroll
        for (int e = 0; e < 2; ++e) {
          stg32(d + e * 256, pk[1][2 * c0 + e]); stg32(d + e * 256 + 128, pk[1][2 * c1 + e]); stg32(d + 512 + e * 128, own ? pk[1][2 * c2 + e] : 0u);
          stg32(d + 6144 + e * 128, pk[2][2 * c0 + e]); stg32(d + 6144 + 256 + e * 128, pk[2][2 * c1 + e]); stg32(d + 6144 + 512 + e * 128, own ? pk[2][2 * c2 + e] : 0x3F803F80u);
        }
        if (h & 1) { __syncwarp(); if (lane == 0) mbar_arrive(BAR(B_KVW + (h >> 1))); }
        if (h == 1) {
          const float f0 = rcp_ap(bhi(lds32(sb + SM_SP + 22528 + (warp * 16 + g) * 4))), f1 = rcp_ap(bhi(lds32(sb + SM_SP + 22528 + (warp * 16 + g + 8) * 4)));
#pragma unroll
          for (int t = 0; t < 10; ++t) packt(0, t, f0 * QSCALE, f1 * QSCALE);
#pragma unroll
          for (int t = 5; t < 10; ++t) { packt(1, t, f0, f1); packt(2, t, f0, f1); }
          const uint32_t qw = sb + SM_QX + warp * 3072 + lane * 8;
#pragma unroll
          for (int hh = 0; hh < 4; ++hh) {
            const int u0 = 5 * (hh >> 1), d0 = (hh & 1) ? u0 + 3 : u0, d2 = u0 + 2;
            const bool ow = (hh & 1) ? (q >= 2) : (q < 2);
            sts64(qw + hh * 768, pk[0][2 * d0], pk[0][2 * d0 + 1]); sts64(qw + hh * 768 + 256, pk[0][2 * d0 + 2], pk[0][2 * d0 + 3]);
            sts64(qw + hh * 768 + 512, ow ? pk[0][2 * d2] : 0x3F803F80u, ow ? pk[0][2 * d2 + 1] : 0x3F803F80u);
          }
          mbar_wait(BAR(B_QDONE), 0);
#pragma unroll
          for (int hh = 0; hh < 4; ++hh) {
            const int u0 = 5 * (hh >> 1), d0 = (hh & 1) ? u0 + 3 : u0, d1 = d0 + 1, d2 = u0 + 2;
            const bool ow = (hh & 1) ? (q >= 2) : (q < 2);
            const uint32_t kd = sb + hh * KVH + 12288 + warp * 768 + lane * 4, vd = kd + 18432;
#pragma unroll
            for (int e = 0; e < 2; ++e) {
              sts32(kd + e * 256, pk[1][2 * d0 + e]); sts32(kd + e * 256 + 128, pk[1][2 * d1 + e]); sts32(kd + 512 + e * 128, ow ? pk[1][2 * d2 + e] : 0u);
              sts32(vd + e * 128, pk[2][2 * d0 + e]); sts32(vd + 256 + e * 128, pk[2][2 * d1 + e]); sts32(vd + 512 + e * 128, ow ? pk[2][2 * d2 + e] : 0x3F803F80u);
            }
          }
          BAR_SYNC(6, 256);
          const uint32_t qr = sb + SM_QX + (warp & 3) * 6144 + wg * 768 + lane * 8;
#pragma unroll
          for (int i = 0; i < 4; ++i)
#pragma unroll
            for (int e = 0; e < 3; ++e) { const uint2 v = lds64(qr + (i & 1) * 3072 + (i >> 1) * 1536 + e * 256); qf[i][2 * e] = v.x; qf[i][2 * e + 1] = v.y; }
        }
      }
    }

    {
      const bool cnd0 = (2 * q <= g), cnd1 = (2 * q + 1 <= g);
      const uint32_t mlast = (cnd0 ? 0xFFFFu : 0u) | (cnd1 ? 0xFFFF0000u : 0u);
      uint32_t ka = sb + wg * KVH + (warp & 3) * 1536 + lane * 16;
      uint8_t* od = g_o + (size_t)(r * 4) * OASZ + j * 10240 + (warp & 3) * 512 + lane * 4;
      float ci[2][4];
      bool exact = false;
      auto qk_tile = [&](float* s, int T, const uint32_t* kf, int e, const float (&c)[4]) {
        mma1688_c(s, qf[T][4], qf[T][5], kf[4 + e], c);
        mma16816(s, qf[T][0], qf[T][1], qf[T][2], qf[T][3], kf[2 * e], kf[2 * e + 1]);
      };
      auto merge = [&](float (&f)[2][4], const float (&l)[2][4]) {
        f[0][0] = cnd0 ? l[0][0] : f[0][0]; f[0][1] = cnd1 ? l[0][1] : f[0][1]; f[0][2] = l[0][2]; f[0][3] = l[0][3];
        f[1][2] = cnd0 ? l[1][2] : f[1][2]; f[1][3] = cnd1 ? l[1][3] : f[1][3];
      };
      auto pv = [&](float (&o)[3][4], uint32_t a0, uint32_t a1, uint32_t a2, uint32_t a3, const uint32_t* vf) {
#pragma unroll
        for (int c = 0; c < 3; ++c) mma16816(o[c], a0, a1, a2, a3, vf[2 * c], vf[2 * c + 1]);
      };
      const float zero4[4] = {0.f, 0.f, 0.f, 0.f};
      int rnd = 0;
#pragma unroll 1
      while (rnd < 2) {
        const int h = 2 * rnd + wg;
        mbar_wait(BAR(B_KVFULL + h), 0);

        float o[2][3][4];
#pragma unroll
        for (int T = 0; T < 2; ++T)
#pragma unroll
          for (int c = 0; c < 3; ++c) { o[T][c][0] = o[T][c][1] = o[T][c][2] = o[T][c][3] = 0.f; }
        float S[2][2][2][4], E[2][2][2][4];
        uint32_t kf[2][6], vf[2][6];
        const uint32_t va = ka + 18432;
        auto ldk = [&](int b, uint32_t a) { ldsm4p(kf[b], a); ldsm2p(kf[b] + 4, a + 512); };
        auto ldv = [&](int b, uint32_t a) { ldsm4tp(vf[b], a); ldsm2tp(vf[b] + 4, a + 512); };
        auto st_qk = [&](int b, int T) { qk_tile(S[b][T][0], T, kf[b], 0, ci[T]); qk_tile(S[b][T][1], T, kf[b], 1, ci[T]); };
        auto st_ex = [&](int b, int T) {
#pragma unroll
          for (int e = 0; e < 2; ++e)
#pragma unroll
            for (int i = 0; i < 4; ++i) E[b][T][e][i] = ex2(S[b][T][e][i]);
        };
        auto cvt = [&](uint32_t (&a)[4], int b, int T) {
          a[0] = pack2(E[b][T][0][0], E[b][T][0][1]); a[1] = pack2(E[b][T][0][2], E[b][T][0][3]);
          a[2] = pack2(E[b][T][1][0], E[b][T][1][1]); a[3] = pack2(E[b][T][1][2], E[b][T][1][3]);
        };
        auto st_pv = [&](int b, int T) { uint32_t a[4]; cvt(a, b, T); pv(o[T], a[0], a[1], a[2], a[3], vf[b]); };
        {
          uint32_t k0[12], kl[12]; float l[2][2][4];
          ldsm4p(k0, ka); ldsm4p(k0 + 4, ka + 512); ldsm4p(k0 + 8, ka + 1024);
          ldsm4p(kl, ka + 8 * 1536); ldsm4p(kl + 4, ka + 8 * 1536 + 512); ldsm4p(kl + 8, ka + 8 * 1536 + 1024);
          ldk(0, ka + 1536); ldk(1, ka + 1536 + 768);
#pragma unroll
          for (int e = 0; e < 2; ++e) {
            qk_tile(S[0][0][e], 0, k0, e, zero4);     qk_tile(l[0][e], 0, kl, e, zero4);
            qk_tile(S[0][1][e], 1, k0 + 6, e, zero4); qk_tile(l[1][e], 1, kl + 6, e, zero4);
          }
#pragma unroll
          for (int T = 0; T < 2; ++T) {
            float (&f)[2][4] = S[0][T];
            merge(f, l[T]);
            float m0 = fmaxf(fmaxf(f[0][0], f[0][1]), fmaxf(f[1][0], f[1][1])), m1 = fmaxf(fmaxf(f[0][2], f[0][3]), fmaxf(f[1][2], f[1][3]));
            m0 = fmaxf(m0, SHX(m0, 1)); m1 = fmaxf(m1, SHX(m1, 1));
            m0 = fmaxf(m0, SHX(m0, 2)); m1 = fmaxf(m1, SHX(m1, 2));
            if (!exact) { ci[T][0] = ci[T][1] = -40.f - m0; ci[T][2] = ci[T][3] = -40.f - m1; }
#pragma unroll
            for (int e = 0; e < 2; ++e)
#pragma unroll
              for (int i = 0; i < 4; ++i) f[e][i] += ci[T][i];
          }
#pragma unroll
          for (int e = 0; e < 2; ++e) { qk_tile(S[1][0][e], 0, k0 + 6, e, ci[0]); qk_tile(S[1][1][e], 1, kl, e, ci[1]); }
        }
        uint32_t vl[2][6];
        ldv(0, va); ldv(1, va + 768);
        ldsm4tp(vl[0], va + 8 * 1536); ldsm2tp(vl[0] + 4, va + 8 * 1536 + 512); ldsm4tp(vl[1], va + 8 * 1536 + 768); ldsm2tp(vl[1] + 4, va + 8 * 1536 + 768 + 512);
#pragma unroll
        for (int b = 0; b < 2; ++b) {
          st_ex(b, 0); st_qk(b, 0); st_ex(b, 1); st_qk(b, 1);
          ldk(b, ka + 2 * 1536 + b * 768);
        }
        {
          uint32_t a[4];
#pragma unroll
          for (int T = 0; T < 2; ++T) {
            cvt(a, 0, T);
            pv(o[T], a[0] & mlast, a[1], 0u, a[3] & mlast, vl[T]);
            pv(o[T], a[0] & ~mlast, 0u, a[2], a[3] & ~mlast, vf[T]);
            st_ex(0, T); st_qk(0, T);
          }
          ldk(0, ka + 3 * 1536); ldv(0, va + 1536);
#pragma unroll
          for (int T = 0; T < 2; ++T) {
            cvt(a, 1, T);
            pv(o[T], a[0], a[1], a[2], a[3], T ? vl[0] : vf[1]);
            st_ex(1, T); st_qk(1, T);
          }
          ldk(1, ka + 3 * 1536 + 768); ldv(1, va + 1536 + 768);
        }
#pragma unroll 1
        for (uint32_t off = 1536; off < 6 * 1536; off += 1536) {
#pragma unroll
          for (int b = 0; b < 2; ++b) {
            st_pv(b, 0); st_ex(b, 0); st_qk(b, 0);
            st_pv(b, 1); st_ex(b, 1); st_qk(b, 1);
            ldk(b, ka + off + 3 * 1536 + b * 768); ldv(b, va + off + 1536 + b * 768);
          }
        }
#pragma unroll
        for (int b = 0; b < 2; ++b) { st_pv(b, 0); st_ex(b, 0); st_pv(b, 1); st_ex(b, 1); ldv(b, va + 7 * 1536 + b * 768); }
#pragma unroll
        for (int b = 0; b < 2; ++b) { st_pv(b, 0); st_pv(b, 1); }
        const int src = (lane & ~3) | (wg ? 0 : 2);
        float ls[2][2];
#pragma unroll
        for (int T = 0; T < 2; ++T) { ls[T][0] = __shfl_sync(0xffffffffu, o[T][2][0], src); ls[T][1] = __shfl_sync(0xffffffffu, o[T][2][2], src); }
        float chk = 0.f;
#pragma unroll
        for (int T = 0; T < 2; ++T)
#pragma unroll
          for (int c = 0; c < 3; ++c) chk += (fabsf(o[T][c][0]) + fabsf(o[T][c][1])) + (fabsf(o[T][c][2]) + fabsf(o[T][c][3]));
        const bool safe = chk <= 1.329228e36f;
        if (!exact && !__all_sync(0xffffffffu, safe)) {
#pragma unroll
          for (int T = 0; T < 2; ++T) {
            float m0 = -INFINITY, m1 = -INFINITY;
#pragma unroll 1
            for (int t = 0; t < 17; ++t) {
              uint32_t kf[6]; float u0[4], u1[4];
              ldsm4p(kf, ka + (t + T) * 768); ldsm2p(kf + 4, ka + (t + T) * 768 + 512);
              qk_tile(u0, T, kf, 0, zero4); qk_tile(u1, T, kf, 1, zero4);
              const bool fst = t == 0, lst = t == 16;
              const bool v0 = fst ? !cnd0 : lst ? cnd0 : true, v1 = fst ? !cnd1 : lst ? cnd1 : true;
              m0 = fmaxf(m0, fmaxf(v0 ? u0[0] : -INFINITY, v1 ? u0[1] : -INFINITY)); m1 = fmaxf(m1, fmaxf(v0 ? u1[2] : -INFINITY, v1 ? u1[3] : -INFINITY));
              m1 = fmaxf(m1, fst ? -INFINITY : fmaxf(u0[2], u0[3])); m0 = fmaxf(m0, lst ? -INFINITY : fmaxf(u1[0], u1[1]));
            }
            m0 = fmaxf(m0, SHX(m0, 1)); m1 = fmaxf(m1, SHX(m1, 1));
            m0 = fmaxf(m0, SHX(m0, 2)); m1 = fmaxf(m1, SHX(m1, 2));
            ci[T][0] = ci[T][1] = -m0; ci[T][2] = ci[T][3] = -m1;
          }
          exact = true;
          continue;
        }
        uint8_t* o0 = od + wg * 6144;
        uint8_t* o2 = od + 4096;
#pragma unroll
        for (int T = 0; T < 2; ++T) {
          const float i0 = rcp_ap(ls[T][0]), i1 = rcp_ap(ls[T][1]);
          stg32(o0 + T * 256, pack2(o[T][0][0] * i0, o[T][0][1] * i0)); stg32(o0 + T * 256 + 128, pack2(o[T][0][2] * i1, o[T][0][3] * i1));
          stg32(o0 + T * 256 + 2048, pack2(o[T][1][0] * i0, o[T][1][1] * i0)); stg32(o0 + T * 256 + 2048 + 128, pack2(o[T][1][2] * i1, o[T][1][3] * i1));
          if (wg ? (q >= 2) : (q < 2)) { stg32(o2 + T * 256, pack2(o[T][2][0] * i0, o[T][2][1] * i0)); stg32(o2 + T * 256 + 128, pack2(o[T][2][2] * i1, o[T][2][3] * i1)); }
        }
        __syncwarp();
        if (lane == 0) mbar_arrive(BAR(B_ODONE + rnd));

        ka += 2 * KVH; od += 2 * OASZ; ++rnd; exact = false;
#pragma unroll
        for (int i = 0; i < 6; ++i) { qf[0][i] = qf[2][i]; qf[1][i] = qf[3][i]; }
      }
    }

    const uint64_t dGA = dadd(mkdesc(SB0, 2048, 128, 0), wg * 1024);
    uint32_t x1[20], aug[4];
    {
      uint32_t gav[10], cbv[10];
      float acc[40];
#pragma unroll
      for (int i = 0; i < 40; ++i) acc[i] = 0.f;
      constexpr uint64_t dB = mkdesc(SB0, 5120, 256, 3);
      uint2 ev[20];
#pragma unroll
      for (int t = 0; t < 20; ++t) x1[t] = xs[t >> 2][t & 3];
#pragma unroll
      for (int t = 0; t < 20; ++t) ev[t] = ld_ll1(modp + 640 + (t / 10) * 640 + 40 * j + 4 * (t % 10) + q);
      const uint4* sp = &g_st2[(r * 8 + 2 * q) * 64 + warp * 8 + g];
#pragma unroll 1
      for (int c = 0; c < 8; ++c) {
        uint32_t ao, bo;
        if (c < 4) {
          mbar_wait(BAR(B_OFULL + (c >> 1)), 0);
          ao = (c < 2 ? 0u : OA1) + (c & 1) * 20480; bo = WOB0 + (c >> 1) * WOBSZ + (c & 1) * 2560;
        } else {
          mbar_wait2(BAR(c == 4 ? oseq(0) : c == 7 ? oseq(3) : 55 + c), 0, BAR(B_OFULL + 2), 0);
          ao = (c < 6 ? OA2 : 0u) + (c & 1) * 20480; bo = __shfl_sync(0xffffffffu, lds32(sb + SM_GB + (c - 4) * 4), 0);
        }

        const uint64_t da = dadd(dGA, ao), db = dadd(dB, bo);
        WG_FENCE();
#pragma unroll
        for (int kk = 0; kk < 5; ++kk) wgmma_ss_n80(acc, dadd(da, kk * 4096), dadd(db, kk * 512));
        WG_COMMIT();
        if (c == 1) { WG_WAIT(0); if (leader) mbar_arrive(BAR(B_WOC0)); }
      }
      {
        bool ok = true;
#pragma unroll
        for (int t = 0; t < 10; ++t) { gav[t] = ev[t].x; cbv[t] = ev[10 + t].x; ok = ok && ev[t].y == tag && ev[10 + t].y == tag; }
        if (!ok) { load_gate(gav, modp + 640 + 40 * j + q, tag); load_gate(cbv, modp + 1280 + 40 * j + q, tag); }
#pragma unroll
        for (int t = 0; t < 10; ++t) {
          cbv[t] = pack2(1.f + blo(cbv[t]), 1.f + bhi(cbv[t]));
        }
        __syncwarp();
      }
      float xf[40], gf[20];
#pragma unroll
      for (int t = 0; t < 20; ++t) {
        xf[2 * t] = blo(x1[t]); xf[2 * t + 1] = bhi(x1[t]); gf[t] = (t & 1) ? bhi(gav[t >> 1]) : blo(gav[t >> 1]);
        asm volatile("" : "+f"(xf[2 * t]), "+f"(xf[2 * t + 1]), "+f"(gf[t]));
      }
      WG_WAIT(0);
      release(B_WODONE);

      uint8_t* hp = g_h2 + (size_t)r * 163840 + j * 20480 + warp * 256 + lane * 4;
#pragma unroll
      for (int t = 0; t < 10; ++t) {
        acc[4 * t] = fmaf(gf[2 * t], acc[4 * t], xf[4 * t]); acc[4 * t + 1] = fmaf(gf[2 * t + 1], acc[4 * t + 1], xf[4 * t + 1]);
        acc[4 * t + 2] = fmaf(gf[2 * t], acc[4 * t + 2], xf[4 * t + 2]); acc[4 * t + 3] = fmaf(gf[2 * t + 1], acc[4 * t + 3], xf[4 * t + 3]);
        x1[2 * t] = pack2(acc[4 * t], acc[4 * t + 1]); x1[2 * t + 1] = pack2(acc[4 * t + 2], acc[4 * t + 3]);
        stg32(hp + t * 2048, hmul2(x1[2 * t], cbv[t])); stg32(hp + t * 2048 + 128, hmul2(x1[2 * t + 1], cbv[t]));
      }
      __syncwarp();
      if (lane == 0) mbar_arrive(BAR(B_X1W));

      const float zz = __uint_as_float(lds32(sb + SM_TAB + 504));
      float s0 = zz, s1 = zz, v0 = zz, v1 = zz, s2 = zz, s3 = zz, v2 = zz, v3 = zz;
#pragma unroll
      for (int t = 0; t < 10; ++t) {
        const float a = acc[4 * t], b = acc[4 * t + 1], c = acc[4 * t + 2], d = acc[4 * t + 3];
        s0 += a; s2 += b; s1 += c; s3 += d;
        v0 = fmaf(a, a, v0); v2 = fmaf(b, b, v2); v1 = fmaf(c, c, v1); v3 = fmaf(d, d, v3);
      }
      s0 += s2; s1 += s3; v0 += v2; v1 += v3;
      s0 += SHX(s0, 1); s1 += SHX(s1, 1); v0 += SHX(v0, 1); v1 += SHX(v1, 1);
      s0 += SHX(s0, 2); s1 += SHX(s1, 2); v0 += SHX(v0, 2); v1 += SHX(v1, 2);
      if (q == 0) st_b128(&g_st2[(r * 8 + j) * 64 + warp * 8 + g], nib_put(s0, tag), nib_put(v0, tag >> 4), nib_put(s1, tag >> 8), nib_put(v1, tag >> 12));
      mbar_wait(BAR(B_KVPUB), 1);
      uint4 p0, p1; uint32_t np = 0;
      do { p0 = ld_b128(sp); p1 = ld_b128(sp + 64); } while (!(nib_ok(p0, tag) && nib_ok(p1, tag)) && ++np < SPIN_LIMIT);
      float m0 = __uint_as_float(p0.x) + __uint_as_float(p1.x), w0 = __uint_as_float(p0.y) + __uint_as_float(p1.y);
      float m1 = __uint_as_float(p0.z) + __uint_as_float(p1.z), w1 = __uint_as_float(p0.w) + __uint_as_float(p1.w);
      m0 += SHX(m0, 1); m1 += SHX(m1, 1); w0 += SHX(w0, 1); w1 += SHX(w1, 1);
      m0 += SHX(m0, 2); m1 += SHX(m1, 2); w0 += SHX(w0, 2); w1 += SHX(w1, 2);
      m0 *= (1.f / D_); m1 *= (1.f / D_);
      const uint32_t sw0 = stat_word(m0, fmaxf(fmaf(w0, 1.f / D_, -m0 * m0), 0.f)), sw1 = stat_word(m1, fmaxf(fmaf(w1, 1.f / D_, -m1 * m1), 0.f));
      set_stat(st, sw0, sw1);
      aug[0] = q < 3 ? sw0 : 0u; aug[1] = q < 3 ? sw1 : 0u; aug[2] = aug[3] = 0u;

    }

    float accA[64], accB[64];
    uint8_t* hd = g_hh + (size_t)(r * 24 + 3 * j) * 16384 + warp * 256 + lane * 4;
    const GeluK gk0 = gelu_consts(st.r0), gk1 = gelu_consts(st.r1);
    {
#pragma unroll
      for (int i = 0; i < 64; ++i) accA[i] = 0.f;
      constexpr uint64_t dB = mkdesc(SB0 + SM_RING, 8192, 1024, 1);
      auto step = [&](float (&acc)[64], int u, int kb, bool zero, bool first) {
        const int slot = u & 3;
        if (first) mbar_wait2(BAR(B_RFULL + slot), (uint32_t)((u >> 2) & 1), BAR(B_AFULL + kb), 1);
        else mbar_wait(BAR(B_RFULL + slot), (uint32_t)((u >> 2) & 1));

        const uint64_t da = dadd(dGA, kb * 16384), db = dadd(dB, slot * GSLOT);
        WG_FENCE();
        if (zero) wgmma_zs_n128(acc, da, db); else wgmma_ss_n128(acc, da, db);
#pragma unroll
        for (int kk = 1; kk < 4; ++kk) wgmma_ss_n128(acc, dadd(da, kk * 4096), dadd(db, kk * 2048));
        WG_COMMIT();
        WG_WAIT(1);
        if (u > 10) release(B_REMPTY + ((u + 3) & 3));
      };
      auto augstep = [&](float (&acc)[64], uint32_t ph) {
        mbar_wait(BAR(B_AUGFULL), ph);
        WG_FENCE();
        wgmma_rs_n128(acc, aug, mkdesc(SB0 + SM_AUG, 0, 128, 0));
      };
#pragma unroll 1
      for (int kb = 0; kb < 9; ++kb) step(accA, 10 + kb, kb, false, true);
      augstep(accA, 1); step(accA, 19, 9, false, true);

#pragma unroll
      for (int kb = 0; kb < 4; ++kb) {
        step(accB, 20 + kb, kb, kb == 0, false);
        if (kb == 0 && leader) mbar_arrive(BAR(B_AUGFREE));
        geglu_tile(accA, 2 * kb, hd, gk0, gk1); geglu_tile(accA, 2 * kb + 1, hd, gk0, gk1);
      }
      __syncwarp(); if (lane == 0) mbar_arrive(BAR(B_HHW));
      augstep(accB, 0);
#pragma unroll 1
      for (int kb = 4; kb < 10; ++kb) { step(accB, 20 + kb, kb, false, false); if (kb == 5 && leader) mbar_arrive(BAR(B_AUGFREE)); }

#pragma unroll
      for (int kb = 0; kb < 4; ++kb) { step(accA, 30 + kb, kb, kb == 0, false); geglu_tile(accB, 2 * kb, hd + 16384, gk0, gk1); geglu_tile(accB, 2 * kb + 1, hd + 16384, gk0, gk1); }
      __syncwarp(); if (lane == 0) mbar_arrive(BAR(B_HHW + 1));
      release(B_AFREE);
      augstep(accA, 1);
#pragma unroll 1
      for (int kb = 4; kb < 10; ++kb) {
        if (kb == 8 && wg == 1) BAR_SYNC(5, 256);
        if (kb == 9 && wg == 0) BAR_ARRIVE(5, 256);
        step(accA, 30 + kb, kb, false, false); if (kb & 1) release(B_AFREE + ((kb - 3) >> 1));
      }
    }

    {
      float acc[80];
      constexpr uint64_t dB = mkdesc(SB0 + 16384, 2048, 512, 2);
      auto step = [&](int slot, uint32_t ph, bool zero) {
        mbar_wait(BAR(B_DFULL + slot), ph);
        const uint64_t da = dadd(dGA, slot * DSTG), db = dadd(dB, slot * DSTG);
        WG_FENCE();
        if (zero) wgmma_zs_n160(acc, da, db); else wgmma_ss_n160(acc, da, db);
#pragma unroll
        for (int kk = 1; kk < 4; ++kk) wgmma_ss_n160(acc, dadd(da, kk * 4096), dadd(db, (kk >> 1) * 10240 + (kk & 1) * 1024));
        WG_COMMIT();
      };
      step(0, 0, true);
      WG_WAIT(1);
      release(B_GUDONE);
#pragma unroll
      for (int t = 0; t < 5; ++t) geglu_tile(accA, t, hd + 32768, gk0, gk1);
      step(1, 0, false);
#pragma unroll
      for (int t = 5; t < 8; ++t) geglu_tile(accA, t, hd + 32768, gk0, gk1);
      __syncwarp(); if (lane == 0) mbar_arrive(BAR(B_HHW + 2));

      WG_WAIT(1);
      release(B_DEMPTY);
      uint32_t gbv[2][10];
      {
        int slot = 2; uint32_t ph = 0;
#pragma unroll 1
        for (int i = 2; i < 12; ++i) {

          if (i == 10 && wg == 1) BAR_SYNC(4, 256);
          step(slot, ph, false);
          if (i == 11 && wg == 0) BAR_ARRIVE(4, 256);
          WG_WAIT(1);
          if (i < 8) release(B_DEMPTY + (slot == 0 ? 4 : slot - 1));
          if (++slot == 5) { slot = 0; ph ^= 1; }
        }
      }
#pragma unroll
      for (int t = 0; t < 10; ++t) gbv[0][t] = lds32(sb + SM_GB + t * 16 + q * 4);
      WG_WAIT(0);

      const uint32_t stg = sb + SM_OST + warp * 5120;
      const uint32_t sad = stg + (uint32_t)((mi & 1) * 8 + l7) * 160 + (uint32_t)(mi >> 1) * 16;
#pragma unroll
      for (int hf = 0; hf < 2; ++hf) {
        const bool own = (j & 1) == hf;
        if (hf) {
#pragma unroll
          for (int t = 0; t < 10; ++t) gbv[1][t] = lds32(sb + SM_GB + 160 + t * 16 + q * 4);
        }
#pragma unroll
        for (int t = 0; t < 10; t += 2) {
          uint32_t ov[4];
#pragma unroll
          for (int e = 0; e < 2; ++e) {
            const float* a = &acc[40 * hf + 4 * (t + e)];
            const float g0 = blo(gbv[hf][t + e]), g1 = bhi(gbv[hf][t + e]);
            const uint32_t xa = own ? x1[2 * (t + e)] : 0u, xb = own ? x1[2 * (t + e) + 1] : 0u;
            ov[2 * e] = pack2(fmaf(g0, a[0], blo(xa)), fmaf(g1, a[1], bhi(xa)));
            ov[2 * e + 1] = pack2(fmaf(g0, a[2], blo(xb)), fmaf(g1, a[3], bhi(xb)));
          }
          stsm4(sad + hf * 2560 + t * 16, ov);
        }
        FENCE_ASYNC_SMEM();
        __syncwarp();
        if (elect()) {
          if (hf == 0) FENCE_ASYNC_GLOBAL();
          tma_add2d(&mOut, stg + hf * 2560, 160 * (j >> 1) + 80 * hf, r * 128 + warp * 16);
          asm volatile("cp.async.bulk.commit_group;" ::: "memory");
          if (hf) asm volatile("cp.async.bulk.wait_group.read 0;" ::: "memory");
        }
      }
      if (tid == 0) g_epoch[bid * 32] = tag;

    }
  }
}

typedef CUresult (*EncodeFn)(CUtensorMap*, CUtensorMapDataType, cuuint32_t, void*, const cuuint64_t*, const cuuint64_t*, const cuuint32_t*,
                             const cuuint32_t*, CUtensorMapInterleave, CUtensorMapSwizzle, CUtensorMapL2promotion, CUtensorMapFloatOOBfill);

void make_map(EncodeFn enc, CUtensorMap* m, const void* base, int rank, const cuuint64_t* dims, const cuuint64_t* strides, const cuuint32_t* box, CUtensorMapSwizzle sw) {
  cuuint32_t es[5] = {1, 1, 1, 1, 1};
  enc(m, CU_TENSOR_MAP_DATA_TYPE_BFLOAT16, rank, const_cast<void*>(base), dims, strides, box, es, CU_TENSOR_MAP_INTERLEAVE_NONE, sw,
      CU_TENSOR_MAP_L2_PROMOTION_L2_128B, CU_TENSOR_MAP_FLOAT_OOB_FILL_NONE);
}

}

extern "C" void kernel_launch(void* const* d_in, const int* in_sizes, int n_in, void* d_out, int out_size) {
  Params P;
  P.x = (const __nv_bfloat16*)d_in[0]; P.wqkv = (const __nv_bfloat16*)d_in[1]; P.wo = (const __nv_bfloat16*)d_in[2];
  P.wg = (const __nv_bfloat16*)d_in[4]; P.wu = (const __nv_bfloat16*)d_in[5]; P.wd = (const __nv_bfloat16*)d_in[6];
  P.c = (const __nv_bfloat16*)d_in[7]; P.wmod = (const __nv_bfloat16*)d_in[8]; P.out = (__nv_bfloat16*)d_out;

  static EncodeFn enc = nullptr;
  if (!enc) {
    cudaDriverEntryPointQueryResult qr;
    cudaGetDriverEntryPoint("cuTensorMapEncodeTiled", (void**)&enc, cudaEnableDefault, &qr);
    cudaFuncSetAttribute(fused_kernel, cudaFuncAttributeMaxDynamicSharedMemorySize, SM_TOTAL);
  }
  CUtensorMap mX, mW64, mW16, mWo, mWg, mWu, mWd, mMod, mMod2, mOut;
  { cuuint64_t d[2] = {640, 2048}, s[1] = {1280}; cuuint32_t b[2] = {80, 16}; make_map(enc, &mOut, P.out, 2, d, s, b, CU_TENSOR_MAP_SWIZZLE_NONE); }
  { cuuint64_t d[2] = {3840, 640}, s[1] = {7680}; cuuint32_t b[2] = {16, 128}, b2[2] = {64, 64}; make_map(enc, &mMod, P.wmod, 2, d, s, b, CU_TENSOR_MAP_SWIZZLE_NONE); make_map(enc, &mMod2, P.wmod, 2, d, s, b2, CU_TENSOR_MAP_SWIZZLE_128B); }
  { cuuint64_t d[2] = {640, 2048}, s[1] = {1280}; cuuint32_t b[2] = {64, 128}; make_map(enc, &mX, P.x, 2, d, s, b, CU_TENSOR_MAP_SWIZZLE_128B); }
  { cuuint64_t d[3] = {640, 640, 3}, s[2] = {3840, 1280}; cuuint32_t b[3] = {64, 32, 3}; make_map(enc, &mW64, P.wqkv, 3, d, s, b, CU_TENSOR_MAP_SWIZZLE_128B); }
  { cuuint64_t d[3] = {640, 640, 3}, s[2] = {3840, 1280}; cuuint32_t b[3] = {16, 32, 3}; make_map(enc, &mW16, P.wqkv, 3, d, s, b, CU_TENSOR_MAP_SWIZZLE_32B); }
  { cuuint64_t d[5] = {16, 40, 8, 40, 2}, s[4] = {1280, 102400, 32, 51200}; cuuint32_t b[5] = {16, 40, 4, 5, 1}; make_map(enc, &mWo, P.wo, 5, d, s, b, CU_TENSOR_MAP_SWIZZLE_32B); }
  { cuuint64_t d[2] = {1536, 640}, s[1] = {3072}; cuuint32_t b[2] = {64, 64}; make_map(enc, &mWg, P.wg, 2, d, s, b, CU_TENSOR_MAP_SWIZZLE_128B); make_map(enc, &mWu, P.wu, 2, d, s, b, CU_TENSOR_MAP_SWIZZLE_128B); }
  { cuuint64_t d[3] = {32, 1536, 20}, s[2] = {1280, 64}; cuuint32_t b[3] = {32, 32, 5}; make_map(enc, &mWd, P.wd, 3, d, s, b, CU_TENSOR_MAP_SWIZZLE_64B); }
  fused_kernel<<<NCTA + NHELP, 384, SM_TOTAL, cudaStreamPerThread>>>(mX, mW64, mW16, mWo, mWg, mWu, mWd, mMod, mMod2, mOut, P);
}
```
